```python
import torch

def _softmax(x, axis=-1):
    return torch.softmax(x, dim=axis)
def _gelu(x):
    return torch.nn.functional.gelu(x, approximate="tanh")
def _silu(x):
    return torch.nn.functional.silu(x)
def _sigmoid(x):
    return torch.sigmoid(x)
def _layernorm(x, axis=-1, eps=1e-5):
    m = x.mean(dim=axis, keepdim=True)
    v = x.var(dim=axis, keepdim=True, unbiased=False)
    return (x - m) / torch.sqrt(v + eps)
def _scatter_add(tgt, idx, src, axis=0):
    return tgt.clone().index_add_(axis, idx, src)
def _segment_sum(src, seg, n):
    out = torch.zeros((n,) + src.shape[1:], dtype=src.dtype)
    return out.index_add_(0, seg, src)
def _pad(x, pw):
    flat = tuple(v for pair in reversed(pw) for v in pair)
    return torch.nn.functional.pad(x, flat)

kernel_name = 'sequential_preLN__mha_block_cached__swiglu_ffn__decode'

def setup_inputs():

    _w = (lambda a: (lambda t: t.to(torch.bfloat16) if t.is_floating_point() else t)(torch.as_tensor(a)))
    def _A_setup():
        B, Sq, D = 1, 1, 640
        H, Sk, Dh = 32, 32768, 192
        return {
            "x": _w((lambda *s: torch.randn(*s, dtype=torch.bfloat16) * 0.05)(B, Sq, D)),
            "k_cache": _w((lambda *s: torch.randn(*s, dtype=torch.bfloat16) * 3.2)(B, H, Sk, Dh)),
            "v_cache": _w((lambda *s: torch.randn(*s, dtype=torch.bfloat16) * 0.4)(B, H, Sk, Dh)),
            "wq": _w((lambda *s: torch.randn(*s, dtype=torch.bfloat16) * 3.2)(D, H * Dh) * (D ** -0.5)),
            "wo": _w((lambda *s: torch.randn(*s, dtype=torch.bfloat16) * 0.4)(H * Dh, D) * ((H * Dh) ** -0.5)),
        }
    _A_in = _A_setup()

    def _B_setup():
        B, S, D, F = 1, 1, 640, 1536
        return {
            "x": _w((lambda *s: torch.randn(*s, dtype=torch.bfloat16) * 0.05)(B, S, D)),
            "w_gate": _w((lambda *s: torch.randn(*s, dtype=torch.bfloat16) * 0.05)(D, F)),
            "w_up": _w((lambda *s: torch.randn(*s, dtype=torch.bfloat16) * 0.05)(D, F)),
            "w_down": _w((lambda *s: torch.randn(*s, dtype=torch.bfloat16) * 0.05)(F, D)),
        }
    _B_in = _B_setup()

    return {
        "A_x": _A_in["x"],
        "A_k_cache": _A_in["k_cache"],
        "A_v_cache": _A_in["v_cache"],
        "A_wq": _A_in["wq"],
        "A_wo": _A_in["wo"],
        "B_x": _B_in["x"],
        "B_w_gate": _B_in["w_gate"],
        "B_w_up": _B_in["w_up"],
        "B_w_down": _B_in["w_down"],
    }

def reference(A_x, A_k_cache, A_v_cache, A_wq, A_wo, B_x, B_w_gate, B_w_up, B_w_down):
    def _A_ref(x, k_cache, v_cache, wq, wo):
        B, Sq, D = x.shape
        H, Dh = 32, 192
        q = (lambda x, *d: x.permute(*d))((x @ wq).reshape(B, Sq, H, Dh), 0, 2, 1, 3)
        scores = torch.einsum("bhqd,bhkd->bhqk", q, k_cache) * (Dh ** -0.5)
        p = _softmax(scores, axis=-1)
        o = torch.einsum("bhqk,bhkd->bhqd", p, v_cache)
        return (lambda x, *d: x.permute(*d))(o, 0, 2, 1, 3).reshape(B, Sq, H * Dh) @ wo

    def _B_ref(x, w_gate, w_up, w_down):
        g = _silu(x @ w_gate)
        u = x @ w_up
        return (g * u) @ w_down

    x = A_x
    h = x + _A_ref(_layernorm(x, axis=-1), A_k_cache, A_v_cache, A_wq, A_wo)
    h2 = h + _B_ref(_layernorm(h, axis=-1), B_w_gate, B_w_up, B_w_down)
    return h2
```

```cpp
#include <cuda_runtime.h>
#include <cuda_bf16.h>
#include <cuda.h>
#include <stdint.h>

namespace {

constexpr int D = 640, H = 32, SK = 32768, DH = 192, F = 1536, HD = H * DH;
constexpr int TILE_KEYS = 32;
constexpr int TILE_BYTES = TILE_KEYS * DH * 2;
constexpr int STAGE_BYTES = 2 * TILE_BYTES;
constexpr int TILES_PER_HEAD = SK / TILE_KEYS;
constexpr int NTILES = H * TILES_PER_HEAD;
#define CFG_NST 4
#define CFG_WQAT 1
#define CFG_W0 2
#define CFG_FW 1
#define CFG_NCOPY 2
constexpr int NST = CFG_NST;
constexpr int G = 128;
constexpr int NC = 4;
constexpr int DC = DH / NC;
constexpr int SLOT_P = 64;
constexpr int RD = 4;
constexpr int NF = 96;
constexpr int NR = 20;
constexpr int NCOPY = CFG_NCOPY;
constexpr int NQ0 = 48;
constexpr int ROWP = D * 2 + 16;
constexpr int WO_BYTES = DC * ROWP;
constexpr int WO_ST = 3;
constexpr int NTHREADS = 320;
constexpr unsigned SPIN_LIMIT = 1u << 24;

constexpr int SM_RING = 0;
constexpr int SM_W = NST * STAGE_BYTES;
constexpr int SM_WU = SM_W + D * 32, SM_WD = SM_W + 2 * D * 32;
constexpr int W_BYTES = 2 * D * 32 + 16 * ROWP;
constexpr int REGA = (SM_W + W_BYTES > WO_ST * WO_BYTES) ? SM_W + W_BYTES : WO_ST * WO_BYTES;
constexpr int SM_Q = (REGA + 127) / 128 * 128;
constexpr int SM_WP = SM_Q + HD * 2;
constexpr int SM_X = SM_WP + 2 * 8 * 200 * 4;
constexpr int SM_XN = SM_X + D * 4;
constexpr int SM_XP = SM_XN + D * 4;
constexpr int SM_BAR = SM_XP + D * 2;
constexpr int SMEM_BYTES = SM_BAR + 256;
static_assert(SMEM_BYTES <= 232448, "smem");
static_assert(NST <= 8 && SM_W % 256 == 0 && CFG_FW < NST && CFG_WQAT <= NST, "stages");

__device__ unsigned g_ticket;
__device__ unsigned g_epoch;
__device__ __align__(256) uint32_t g_q0[4 * DH];
__device__ __align__(256) uint32_t g_q[HD];
__device__ __align__(256) uint32_t g_part[RD * NC * G * SLOT_P];
__device__ __align__(256) uint32_t g_h2[NCOPY * NC * D];
__device__ __align__(256) uint32_t g_h3[NR * NF * 32];

#define TS(k) do { } while (0)
#define CKDECL do { } while (0)
#define CKS(k) do { } while (0)
#define CKDUMP() do { } while (0)

__device__ __forceinline__ uint32_t smem_u32(const void* p) { return (uint32_t)__cvta_generic_to_shared(p); }
__device__ __forceinline__ void mbar_init(uint32_t bar, uint32_t cnt) {
    asm volatile("mbarrier.init.shared::cta.b64 [%0], %1;" ::"r"(bar), "r"(cnt) : "memory");
}
__device__ __forceinline__ void mbar_expect_tx(uint32_t bar, uint32_t bytes) {
    asm volatile("mbarrier.arrive.expect_tx.shared::cta.b64 _, [%0], %1;" ::"r"(bar), "r"(bytes) : "memory");
}
__device__ __forceinline__ void mbar_arrive(uint32_t bar) {
    asm volatile("mbarrier.arrive.shared::cta.b64 _, [%0];" ::"r"(bar) : "memory");
}
__device__ __forceinline__ void mbar_wait(uint32_t bar, uint32_t parity) {
    uint32_t done;
    unsigned it = 0;
    while (true) {
        asm volatile("{\n.reg .pred p;\nmbarrier.try_wait.parity.shared::cta.b64 p, [%1], %2;\nselp.u32 %0, 1, 0, p;\n}"
                     : "=r"(done) : "r"(bar), "r"(parity) : "memory");
        if (done) break;
        if (++it > SPIN_LIMIT) __trap();
    }
}
__device__ __forceinline__ void bulk_load(uint32_t dst, const void* src, uint32_t bytes, uint32_t bar, uint64_t pol) {
    asm volatile("cp.async.bulk.shared::cluster.global.mbarrier::complete_tx::bytes.L2::cache_hint [%0], [%1], %2, [%3], %4;"
                 ::"r"(dst), "l"(src), "r"(bytes), "r"(bar), "l"(pol) : "memory");
}
__device__ __forceinline__ void tensor_load2d(uint32_t dst, const CUtensorMap* tm, int c0, int c1, uint32_t bar, uint64_t pol) {
    asm volatile("cp.async.bulk.tensor.2d.shared::cluster.global.mbarrier::complete_tx::bytes.L2::cache_hint [%0], [%1, {%2, %3}], [%4], %5;"
                 ::"r"(dst), "l"(tm), "r"(c0), "r"(c1), "r"(bar), "l"(pol) : "memory");
}
__device__ __forceinline__ void cbar() { asm volatile("bar.sync 1, 256;" ::: "memory"); }

__device__ __forceinline__ uint4 ldg_nc4(const void* p) {
    uint4 v;
    asm volatile("ld.global.nc.L1::no_allocate.v4.u32 {%0,%1,%2,%3}, [%4];" : "=r"(v.x), "=r"(v.y), "=r"(v.z), "=r"(v.w) : "l"(p));
    return v;
}
__device__ __forceinline__ uint2 ldg_nc2(const void* p) {
    uint2 v;
    asm volatile("ld.global.nc.L1::no_allocate.v2.u32 {%0,%1}, [%2];" : "=r"(v.x), "=r"(v.y) : "l"(p));
    return v;
}
__device__ __forceinline__ uint4 mb_ld4(const uint32_t* p) {
    uint4 v;
    asm volatile("ld.relaxed.gpu.global.v4.u32 {%0,%1,%2,%3}, [%4];" : "=r"(v.x), "=r"(v.y), "=r"(v.z), "=r"(v.w) : "l"(p) : "memory");
    return v;
}
__device__ __forceinline__ uint32_t mb_ld(const uint32_t* p) {
    uint32_t v;
    asm volatile("ld.relaxed.gpu.global.u32 %0, [%1];" : "=r"(v) : "l"(p) : "memory");
    return v;
}
__device__ __forceinline__ void mb_st4(uint32_t* p, uint4 v) {
    asm volatile("st.relaxed.gpu.global.v4.u32 [%0], {%1,%2,%3,%4};" ::"l"(p), "r"(v.x), "r"(v.y), "r"(v.z), "r"(v.w) : "memory");
}
__device__ __forceinline__ void mb_st(uint32_t* p, uint32_t v) {
    asm volatile("st.relaxed.gpu.global.u32 [%0], %1;" ::"l"(p), "r"(v) : "memory");
}
__device__ __forceinline__ uint32_t mb_enc(float f, uint32_t tag) { return (__float_as_uint(f) & ~1u) | tag; }
__device__ __forceinline__ uint4 mb_enc4(uint4 v, uint32_t tag) {
    return make_uint4((v.x & ~1u) | tag, (v.y & ~1u) | tag, (v.z & ~1u) | tag, (v.w & ~1u) | tag);
}
__device__ __forceinline__ uint32_t mb_miss(uint4 v, uint32_t tag) { return ((v.x ^ tag) | (v.y ^ tag) | (v.z ^ tag) | (v.w ^ tag)) & 1u; }
template <int N>
__device__ __forceinline__ void mb_poll(uint4 (&a)[N], const uint32_t* p, int stride, uint32_t tag, bool active = true) {
    const uint32_t init = active ? tag ^ 1u : tag;
#pragma unroll
    for (int i = 0; i < N; i++) a[i] = make_uint4(init, init, init, init);
    unsigned it = 0;
    while (true) {
        uint32_t miss = 0u;
#pragma unroll
        for (int i = 0; i < N; i++) if (mb_miss(a[i], tag)) a[i] = mb_ld4(p + i * stride);
#pragma unroll
        for (int i = 0; i < N; i++) miss |= mb_miss(a[i], tag);
        if (!miss) break;
        if (++it > SPIN_LIMIT) __trap();
    }
}
#define F4SUM(v, c) ((__uint_as_float(v[0].c) + __uint_as_float(v[1].c)) + (__uint_as_float(v[2].c) + __uint_as_float(v[3].c)))

__device__ __forceinline__ float bf_lo(uint32_t w) { return __uint_as_float(w << 16); }
__device__ __forceinline__ float bf_hi(uint32_t w) { return __uint_as_float(w & 0xffff0000u); }
__device__ __forceinline__ float bfr(float f) { return __bfloat162float(__float2bfloat16_rn(f)); }
__device__ __forceinline__ uint32_t pack_bf2(float lo, float hi) {
    uint32_t r;
    asm("cvt.rn.bf16x2.f32 %0, %1, %2;" : "=r"(r) : "f"(hi), "f"(lo));
    return r;
}
__device__ __forceinline__ float ex2(float x) { float y; asm("ex2.approx.ftz.f32 %0, %1;" : "=f"(y) : "f"(x)); return y; }
__device__ __forceinline__ float rcp(float x) { float y; asm("rcp.approx.ftz.f32 %0, %1;" : "=f"(y) : "f"(x)); return y; }
__device__ __forceinline__ uint4 lds4(uint32_t a) {
    uint4 v;
    asm volatile("ld.shared.v4.u32 {%0,%1,%2,%3}, [%4];" : "=r"(v.x), "=r"(v.y), "=r"(v.z), "=r"(v.w) : "r"(a) : "memory");
    return v;
}
__device__ __forceinline__ uint4 ldsm4t(uint32_t a) {
    uint4 v;
    asm volatile("ldmatrix.sync.aligned.m8n8.x4.trans.shared.b16 {%0,%1,%2,%3}, [%4];" : "=r"(v.x), "=r"(v.y), "=r"(v.z), "=r"(v.w) : "r"(a) : "memory");
    return v;
}
__device__ __forceinline__ void mma16816(float* d, uint4 a, uint32_t b0, uint32_t b1) {
    asm volatile("mma.sync.aligned.m16n8k16.row.col.f32.bf16.bf16.f32 {%0,%1,%2,%3}, {%4,%5,%6,%7}, {%8,%9}, {%0,%1,%2,%3};"
                 : "+f"(d[0]), "+f"(d[1]), "+f"(d[2]), "+f"(d[3]) : "r"(a.x), "r"(a.y), "r"(a.z), "r"(a.w), "r"(b0), "r"(b1));
}
__device__ __forceinline__ void fma8(float* acc, float s, uint4 w) {
    acc[0] = fmaf(s, bf_lo(w.x), acc[0]); acc[1] = fmaf(s, bf_hi(w.x), acc[1]);
    acc[2] = fmaf(s, bf_lo(w.y), acc[2]); acc[3] = fmaf(s, bf_hi(w.y), acc[3]);
    acc[4] = fmaf(s, bf_lo(w.z), acc[4]); acc[5] = fmaf(s, bf_hi(w.z), acc[5]);
    acc[6] = fmaf(s, bf_lo(w.w), acc[6]); acc[7] = fmaf(s, bf_hi(w.w), acc[7]);
}
__device__ __forceinline__ void ln_finish(float mean, float var, float& mean_b, float& rden) {
    mean_b = bfr(mean);
    float sq;
    asm("sqrt.approx.ftz.f32 %0, %1;" : "=f"(sq) : "f"(bfr(bfr(fmaxf(var, 0.f)) + 1e-5f)));
    rden = rcp(bfr(sq));
}
__device__ __forceinline__ uint4 tiles_to_rows(const float (&d)[5][4], float* stage, int lane, uint32_t tag) {
    const int g8 = lane >> 2, c4 = lane & 3;
    stage[c4 * 16 + g8] = c4 == 0 ? d[0][0] : c4 == 1 ? d[1][0] : c4 == 2 ? d[2][0] : d[3][0];
    stage[c4 * 16 + 8 + g8] = c4 == 0 ? d[0][2] : c4 == 1 ? d[1][2] : c4 == 2 ? d[2][2] : d[3][2];
    if (c4 < 2) stage[64 + c4 * 8 + g8] = c4 == 0 ? d[4][0] : d[4][2];
    __syncwarp();
    return mb_enc4(reinterpret_cast<const uint4*>(stage)[lane < 20 ? lane : 0], tag);
}

#define CFG_DRY 0
__device__ __forceinline__ int first_pass() { int v; asm volatile("mov.u32 %0, %1;" : "=r"(v) : "n"(CFG_DRY ? 0 : 1)); return v; }

struct alignas(64) Params {
    CUtensorMap tm_wq, tm_wg, tm_wu;
    const __nv_bfloat16 *x, *k, *v, *wq, *wo, *wd;
    __nv_bfloat16* out;
};

__global__ void __launch_bounds__(NTHREADS, 1) fused_decode_kernel(const __grid_constant__ Params p) {
    extern __shared__ __align__(1024) unsigned char smem[];
    const int tid = threadIdx.x, warp = tid >> 5, lane = tid & 31, bid = blockIdx.x;
    const uint32_t sbase = smem_u32(smem);
    const uint32_t bar_full = sbase + SM_BAR, bar_empty = sbase + SM_BAR + 64;
    const uint32_t bar_wq = sbase + SM_BAR + 192, bar_ffn = bar_wq + 16, bar_q0 = bar_wq + 24;
    volatile int* s_tile = reinterpret_cast<volatile int*>(smem + SM_BAR + 128);
    volatile int* s_qready = s_tile + 8;
    volatile uint32_t* s_tag = reinterpret_cast<volatile uint32_t*>(s_tile + 9);
    float* s_wp = reinterpret_cast<float*>(smem + SM_WP);
    float* s_x = reinterpret_cast<float*>(smem + SM_X);
    float* s_xn = reinterpret_cast<float*>(smem + SM_XN);
    const bool streaming = bid < G;
    const char* kb = reinterpret_cast<const char*>(p.k);
    const char* vb = reinterpret_cast<const char*>(p.v);

    if (tid == 0) TS(0);
    CKDECL;
    if (warp == 8) {
        uint64_t pol = 0;
        unsigned nxt = 0;
        if (lane == 0) {
            if (streaming) asm volatile("atom.relaxed.gpu.global.add.u32 %0, [%1], 1;" : "=r"(nxt) : "l"(&g_ticket) : "memory");
            asm volatile("createpolicy.fractional.L2::evict_first.b64 %0, 1.0;" : "=l"(pol));
#pragma unroll
            for (int i = 0; i < 8; i++) { mbar_init(bar_full + 8 * i, 1); mbar_init(bar_empty + 8 * i, 8); }
#pragma unroll
            for (int i = 0; i < 4; i++) mbar_init(bar_wq + 8 * i, 1);
            *s_qready = 0;
            asm volatile("fence.mbarrier_init.release.cluster;" ::: "memory");
        }
        __syncwarp();
        asm volatile("bar.arrive 2, %0;" ::"n"(NTHREADS) : "memory");
        if (lane != 0) return;
        if (streaming) {
#pragma unroll
            for (int i = 0; i < NST + 2; i++) {
                if (i >= CFG_W0) {
                    const int w = i - CFG_W0;
                    mbar_wait(w < CFG_WQAT ? bar_full + 8 * w : w < CFG_WQAT + 2 ? bar_wq + 8 * (w - CFG_WQAT) : bar_full + 8 * (w - 2), 0);
                }
                if (i >= CFG_WQAT && i < CFG_WQAT + 2) {
                    const int hf = i - CFG_WQAT;
                    mbar_expect_tx(bar_wq + 8 * hf, 320 * 96);
#pragma unroll
                    for (int r = 2 * hf; r < 2 * hf + 2; r++)
                        tensor_load2d(sbase + SM_W + r * 160 * 96, &p.tm_wq, bid * 48, r * 160, bar_wq + 8 * hf, pol);
                } else {
                    const int sg = i < CFG_WQAT ? i : i - 2;
                    const unsigned t = sg * G + bid;
                    s_tile[sg] = (int)t;
                    mbar_expect_tx(bar_full + 8 * sg, STAGE_BYTES);
                    bulk_load(sbase + SM_RING + sg * STAGE_BYTES, kb + (size_t)t * TILE_BYTES, TILE_BYTES, bar_full + 8 * sg, pol);
                    bulk_load(sbase + SM_RING + sg * STAGE_BYTES + TILE_BYTES, vb + (size_t)t * TILE_BYTES, TILE_BYTES, bar_full + 8 * sg, pol);
                }
            }
            int st = 0;
            uint32_t ph = 0;
            while (true) {
                mbar_wait(bar_empty + 8 * st, ph);
                const unsigned t = NST * G + nxt;
                if (t >= NTILES) break;
                asm volatile("atom.relaxed.gpu.global.add.u32 %0, [%1], 1;" : "=r"(nxt) : "l"(&g_ticket) : "memory");
                s_tile[st] = (int)t;
                mbar_expect_tx(bar_full + 8 * st, STAGE_BYTES);
                const uint32_t dst = sbase + SM_RING + st * STAGE_BYTES;
                bulk_load(dst, kb + (size_t)t * TILE_BYTES, TILE_BYTES, bar_full + 8 * st, pol);
                bulk_load(dst + TILE_BYTES, vb + (size_t)t * TILE_BYTES, TILE_BYTES, bar_full + 8 * st, pol);
                if (++st == NST) { st = 0; ph ^= 1; }
            }
            s_tile[st] = NTILES;
            mbar_arrive(bar_full + 8 * st);
            TS(2);
            if (bid < NF) {
                unsigned it = 0;
                while (*s_qready < H) { if (++it > SPIN_LIMIT) __trap(); }
                if (CFG_FW > 0) {
                    const int s2 = st - CFG_FW;
                    mbar_wait(bar_full + 8 * (s2 < 0 ? s2 + NST : s2), s2 < 0 ? ph : ph ^ 1);
                }
                mbar_expect_tx(bar_ffn, 2 * D * 32 + 16 * D * 2);
#pragma unroll 1
                for (int r = 0; r < 4; r++) {
                    tensor_load2d(sbase + SM_W + r * 160 * 32, &p.tm_wg, bid * 16, r * 160, bar_ffn, pol);
                    tensor_load2d(sbase + SM_WU + r * 160 * 32, &p.tm_wu, bid * 16, r * 160, bar_ffn, pol);
                }
#pragma unroll 1
                for (int r = 0; r < 16; r++)
                    bulk_load(sbase + SM_WD + r * ROWP, p.wd + (size_t)(bid * 16 + r) * D, D * 2, bar_ffn, pol);
            }
        } else {
            int st = 0;
            uint32_t ph = 1;
            for (int h = 0; h < H; h++) {
                if (h >= WO_ST) mbar_wait(bar_empty + 8 * st, ph);
                mbar_expect_tx(bar_full + 8 * st, DC * D * 2);
#pragma unroll 1
                for (int r = 0; r < DC; r++)
                    bulk_load(sbase + SM_RING + st * WO_BYTES + r * ROWP, p.wo + (size_t)(h * DH + (bid - G) * DC + r) * D, D * 2,
                              bar_full + 8 * st, pol);
                if (++st == WO_ST) { st = 0; ph ^= 1; }
            }
        }
        return;
    }
    if (warp == 9) {
        uint2 xraw[5];
        uint4 w0[10];
        if (streaming) {
#pragma unroll
            for (int i = 0; i < 5; i++) xraw[i] = ldg_nc2(p.x + (i * 32 + lane) * 4);
            if (bid < NQ0) {
                const __nv_bfloat16* src = p.wq + (size_t)((bid / 12) * 160 + (lane >> 1)) * HD + (bid % 12) * 16 + (lane & 1) * 8;
#pragma unroll
                for (int i = 0; i < 10; i++) w0[i] = ldg_nc4(src + (size_t)i * 16 * HD);
            }
        }
        const uint32_t epoch = mb_ld(&g_epoch);
        asm volatile("bar.sync 2, %0;" ::"n"(NTHREADS) : "memory");
        const uint32_t tag = (epoch & 1u) ^ 1u;
        if (lane == 0) *s_tag = tag;
        if (!streaming) {
            __syncwarp();
            if (lane == 0) mbar_arrive(bar_q0);
            return;
        }
        uint32_t* s_xp = reinterpret_cast<uint32_t*>(smem + SM_XP);
        uint2* s_q = reinterpret_cast<uint2*>(smem + SM_Q);
        {
            float4 xv[5];
#pragma unroll
            for (int i = 0; i < 5; i++) xv[i] = make_float4(bf_lo(xraw[i].x), bf_hi(xraw[i].x), bf_lo(xraw[i].y), bf_hi(xraw[i].y));
            const float s0 = __shfl_sync(0xffffffffu, xv[0].x, 0);
            float s1 = 0.f, s2 = 0.f;
#pragma unroll
            for (int i = 0; i < 5; i++) {
                const float a = xv[i].x - s0, b = xv[i].y - s0, c = xv[i].z - s0, d = xv[i].w - s0;
                s1 += (a + b) + (c + d);
                s2 += (a * a + b * b) + (c * c + d * d);
            }
#pragma unroll
            for (int o = 16; o > 0; o >>= 1) {
                s1 += __shfl_xor_sync(0xffffffffu, s1, o);
                s2 += __shfl_xor_sync(0xffffffffu, s2, o);
            }
            const float e1 = s1 * (1.0f / D);
            float mb, rden;
            ln_finish(s0 + e1, s2 * (1.0f / D) - e1 * e1, mb, rden);
#pragma unroll
            for (int i = 0; i < 5; i++) {
                const uint32_t lo = pack_bf2(bfr(xv[i].x - mb) * rden, bfr(xv[i].y - mb) * rden);
                const uint32_t hi = pack_bf2(bfr(xv[i].z - mb) * rden, bfr(xv[i].w - mb) * rden);
                reinterpret_cast<float4*>(s_x)[i * 32 + lane] = xv[i];
                reinterpret_cast<float4*>(s_xn)[i * 32 + lane] = make_float4(bf_lo(lo), bf_hi(lo), bf_lo(hi), bf_hi(hi));
                reinterpret_cast<uint2*>(s_xp)[i * 32 + lane] = make_uint2(lo, hi);
            }
            __syncwarp();
        }
        if (lane == 0) TS(8);
        if (bid < NQ0) {
            float acc[8] = {0.f, 0.f, 0.f, 0.f, 0.f, 0.f, 0.f, 0.f};
#pragma unroll
            for (int i = 0; i < 10; i++) fma8(acc, s_xn[(bid / 12) * 160 + (lane >> 1) + 16 * i], w0[i]);
            const bool u1 = lane & 16, u2 = lane & 8, u3 = lane & 4;
            float r4[4], r2[2];
#pragma unroll
            for (int i = 0; i < 4; i++) r4[i] = (u1 ? acc[i + 4] : acc[i]) + __shfl_xor_sync(0xffffffffu, u1 ? acc[i] : acc[i + 4], 16);
#pragma unroll
            for (int i = 0; i < 2; i++) r2[i] = (u2 ? r4[i + 2] : r4[i]) + __shfl_xor_sync(0xffffffffu, u2 ? r4[i] : r4[i + 2], 8);
            float r1 = (u3 ? r2[1] : r2[0]) + __shfl_xor_sync(0xffffffffu, u3 ? r2[0] : r2[1], 4);
            r1 += __shfl_xor_sync(0xffffffffu, r1, 2);
            if (!(lane & 2))
                mb_st(&g_q0[(bid / 12) * DH + (bid % 12) * 16 + (lane & 1) * 8 + (u1 ? 4 : 0) + (u2 ? 2 : 0) + (u3 ? 1 : 0)], mb_enc(r1, tag));
        }
        {
            uint4 a[4], b[4];
            mb_poll(a, g_q0 + lane * 4, DH, tag);
            mb_poll(b, g_q0 + 128 + lane * 4, DH, tag, lane < 16);
            s_q[lane] = make_uint2(pack_bf2(F4SUM(a, x), F4SUM(a, y)), pack_bf2(F4SUM(a, z), F4SUM(a, w)));
            if (lane < 16) s_q[32 + lane] = make_uint2(pack_bf2(F4SUM(b, x), F4SUM(b, y)), pack_bf2(F4SUM(b, z), F4SUM(b, w)));
            __syncwarp();
            if (lane == 0) { mbar_arrive(bar_q0); TS(1); }
        }
        mbar_wait(bar_wq, 0);
        mbar_wait(bar_wq + 8, 0);
        {
            const int g8 = lane >> 2, c4 = lane & 3, mj = lane >> 3, mr = lane & 7;
            float dq[3][4];
#pragma unroll
            for (int t = 0; t < 3; t++) dq[t][0] = dq[t][1] = dq[t][2] = dq[t][3] = 0.f;
            const uint32_t a0 = sbase + SM_W + ((mj >> 1) * 8 + mr) * 96 + (mj & 1) * 16;
#pragma unroll 4
            for (int s = 0; s < 40; s++) {
                const uint32_t b0 = s_xp[s * 8 + c4], b1 = s_xp[s * 8 + 4 + c4];
#pragma unroll
                for (int t = 0; t < 3; t++) mma16816(dq[t], ldsm4t(a0 + s * 16 * 96 + t * 32), b0, b1);
            }
            if (c4 < 3) {
                const float v0 = c4 == 0 ? dq[0][0] : c4 == 1 ? dq[1][0] : dq[2][0];
                const float v1 = c4 == 0 ? dq[0][2] : c4 == 1 ? dq[1][2] : dq[2][2];
                mb_st(&g_q[bid * 48 + c4 * 16 + g8], mb_enc(bfr(v0), tag));
                mb_st(&g_q[bid * 48 + c4 * 16 + 8 + g8], mb_enc(bfr(v1), tag));
            }
        }
        if (lane == 0) TS(9);
#pragma unroll 1
        for (int h0 = 1; h0 < H; h0 = (h0 + 4) & ~3) {
            const int nv = (h0 == 1 ? 3 : 4) * (DH / 4);
            uint4 a[6];
#pragma unroll
            for (int i = 0; i < 6; i++) {
                uint4 t1[1];
                t1[0] = make_uint4(tag, tag, tag, tag);
                if (i * 32 + lane < nv) t1[0] = mb_ld4(g_q + (h0 * (DH / 4) + i * 32 + lane) * 4);
                a[i] = t1[0];
            }
            unsigned it = 0;
            while (true) {
                uint32_t miss = 0u;
#pragma unroll
                for (int i = 0; i < 6; i++) miss |= mb_miss(a[i], tag);
                if (!miss) break;
#pragma unroll
                for (int i = 0; i < 6; i++) if (mb_miss(a[i], tag)) a[i] = mb_ld4(g_q + (h0 * (DH / 4) + i * 32 + lane) * 4);
                if (++it > SPIN_LIMIT) __trap();
            }
#pragma unroll
            for (int i = 0; i < 6; i++)
                if (i * 32 + lane < nv)
                    s_q[h0 * (DH / 4) + i * 32 + lane] = make_uint2((a[i].x >> 16) | (a[i].y & 0xffff0000u), (a[i].z >> 16) | (a[i].w & 0xffff0000u));
            __syncwarp();
            if (lane == 0) {
                asm volatile("fence.acq_rel.cta;" ::: "memory");
                *s_qready = (h0 + 4) & ~3;
                if (h0 == 1) TS(10);
            }
        }
        if (lane == 0) TS(12);
        return;
    }
    asm volatile("bar.sync 2, %0;" ::"n"(NTHREADS) : "memory");

    if (streaming) {
        const int j = lane & 7;
        const uint32_t row_off = (warp * 4 + (lane >> 3)) * (DH * 2) + j * 16;
        const int mb_c = tid < DH ? tid / DC : (tid - DH) >> 3;
        const int mb_w = tid < DH ? tid % DC : DC + ((tid - DH) & 7);
        const bool mb_owner = tid < DH + 8 * NC, mb_check = mb_owner && mb_w < DC + 4;
        uint32_t* const mb_base = g_part + (mb_c * G + bid) * SLOT_P + mb_w;
        uint32_t chk = mb_check ? mb_ld(mb_base) : 0u;

        float q[24], o[24];
        float m = -3.0e38f, l = 0.f;
#pragma unroll
        for (int i = 0; i < 24; i++) o[i] = 0.f;
        int head = -1;
        int st = 0;
        uint32_t ph = 0;
        mbar_wait(bar_q0, 0);
        while (true) {
            mbar_wait(bar_full + 8 * st, ph);
            const int th = s_tile[st] / TILES_PER_HEAD;
            const uint32_t ka = sbase + SM_RING + st * STAGE_BYTES + row_off;
            uint4 kv[3], vv[3];
            if (th < H) {
#pragma unroll
                for (int c = 0; c < 3; c++) kv[c] = lds4(ka + c * 128);
#pragma unroll
                for (int c = 0; c < 3; c++) vv[c] = lds4(ka + TILE_BYTES + c * 128);
                __syncwarp();
                if (lane == 0) mbar_arrive(bar_empty + 8 * st);
            }
            if (++st == NST) { st = 0; ph ^= 1; }

            if (th != head) {
                if (th == H && tid == 0) TS(3);
                CKS(0);
                if (head < 0) head = 0;
#pragma unroll 1
                for (; head < th; head++) {
                    float M = fmaxf(m, __shfl_xor_sync(0xffffffffu, m, 8));
                    M = fmaxf(M, __shfl_xor_sync(0xffffffffu, M, 16));
                    const float f = ex2(m - M);
                    float ls = l * f;
                    ls += __shfl_xor_sync(0xffffffffu, ls, 8);
                    ls += __shfl_xor_sync(0xffffffffu, ls, 16);
                    const bool u1 = lane & 16, u2 = lane & 8;
                    float r[12], z[6];
#pragma unroll
                    for (int i = 0; i < 12; i++) {
                        const float a = o[i] * f, b = o[i + 12] * f;
                        r[i] = (u1 ? b : a) + __shfl_xor_sync(0xffffffffu, u1 ? a : b, 16);
                    }
#pragma unroll
                    for (int i = 0; i < 6; i++) z[i] = (u2 ? r[i + 6] : r[i]) + __shfl_xor_sync(0xffffffffu, u2 ? r[i] : r[i + 6], 8);
                    float* wp = s_wp + (head & 1) * 1600;
                    const int ib = (u1 ? 12 : 0) + (u2 ? 6 : 0);
#pragma unroll
                    for (int i = 0; i < 6; i++) {
                        const int idx = ib + i;
                        wp[warp * 196 + (idx >> 3) * 64 + j * 8 + (idx & 7)] = z[i];
                    }
                    if (lane == 0) { wp[warp * 196 + 192] = ls; wp[1568 + warp] = M; }
                    CKS(1);
                    cbar();
                    if (mb_owner) {
                        const float4 m0 = reinterpret_cast<const float4*>(wp + 1568)[0], m1 = reinterpret_cast<const float4*>(wp + 1568)[1];
                        const float mw[8] = {m0.x, m0.y, m0.z, m0.w, m1.x, m1.y, m1.z, m1.w};
                        float M8 = fmaxf(fmaxf(fmaxf(mw[0], mw[1]), fmaxf(mw[2], mw[3])), fmaxf(fmaxf(mw[4], mw[5]), fmaxf(mw[6], mw[7])));
                        M8 = __uint_as_float(mb_enc(M8, 1u));
                        const int col = tid < DH ? tid : 192;
                        float s0 = 0.f, s1 = 0.f;
#pragma unroll
                        for (int w = 0; w < 8; w += 2) {
                            s0 = fmaf(ex2(mw[w] - M8), wp[w * 196 + col], s0);
                            s1 = fmaf(ex2(mw[w + 1] - M8), wp[(w + 1) * 196 + col], s1);
                        }
                        uint32_t* dst = mb_base + (head % RD) * (NC * G * SLOT_P);
                        unsigned it = 0;
                        while (chk != 0u) { chk = mb_ld(dst); if (++it > SPIN_LIMIT) __trap(); }
                        mb_st(dst, mb_enc(mb_w == DC + 1 ? M8 : s0 + s1, 1u));
                        if (mb_check && head + 1 < H) chk = mb_ld(mb_base + ((head + 1) % RD) * (NC * G * SLOT_P));
                    }
                    m = -3.0e38f; l = 0.f;
#pragma unroll
                    for (int i = 0; i < 24; i++) o[i] = 0.f;
                }
                if (th == H) break;
                if (head > 0) {
                    unsigned it = 0;
                    while (*s_qready <= head) { if (++it > SPIN_LIMIT) __trap(); }
                    asm volatile("fence.acq_rel.cta;" ::: "memory");
                }
#pragma unroll
                for (int c = 0; c < 3; c++) {
                    const uint4 u = lds4(sbase + SM_Q + head * (DH * 2) + c * 128 + j * 16);
                    q[c * 8 + 0] = bf_lo(u.x); q[c * 8 + 1] = bf_hi(u.x); q[c * 8 + 2] = bf_lo(u.y); q[c * 8 + 3] = bf_hi(u.y);
                    q[c * 8 + 4] = bf_lo(u.z); q[c * 8 + 5] = bf_hi(u.z); q[c * 8 + 6] = bf_lo(u.w); q[c * 8 + 7] = bf_hi(u.w);
                }
            }
            float d0 = 0.f, d1 = 0.f, d2 = 0.f, d3 = 0.f;
#pragma unroll
            for (int c = 0; c < 3; c++) {
                d0 = fmaf(q[c * 8 + 0], bf_lo(kv[c].x), d0); d1 = fmaf(q[c * 8 + 1], bf_hi(kv[c].x), d1);
                d2 = fmaf(q[c * 8 + 2], bf_lo(kv[c].y), d2); d3 = fmaf(q[c * 8 + 3], bf_hi(kv[c].y), d3);
                d0 = fmaf(q[c * 8 + 4], bf_lo(kv[c].z), d0); d1 = fmaf(q[c * 8 + 5], bf_hi(kv[c].z), d1);
                d2 = fmaf(q[c * 8 + 6], bf_lo(kv[c].w), d2); d3 = fmaf(q[c * 8 + 7], bf_hi(kv[c].w), d3);
            }
            float s = (d0 + d1) + (d2 + d3);
            s += __shfl_xor_sync(0xffffffffu, s, 1);
            s += __shfl_xor_sync(0xffffffffu, s, 2);
            s += __shfl_xor_sync(0xffffffffu, s, 4);
            s = bfr(bfr(s) * 0.07216878364870322f) * 1.4426950408889634f;
            const float mn = fmaxf(m, s);
            const float al = ex2(m - mn), pr = ex2(s - mn);
            m = mn;
            l = fmaf(l, al, pr);
#pragma unroll
            for (int c = 0; c < 3; c++) {
                o[c * 8 + 0] = fmaf(pr, bf_lo(vv[c].x), o[c * 8 + 0] * al); o[c * 8 + 1] = fmaf(pr, bf_hi(vv[c].x), o[c * 8 + 1] * al);
                o[c * 8 + 2] = fmaf(pr, bf_lo(vv[c].y), o[c * 8 + 2] * al); o[c * 8 + 3] = fmaf(pr, bf_hi(vv[c].y), o[c * 8 + 3] * al);
                o[c * 8 + 4] = fmaf(pr, bf_lo(vv[c].z), o[c * 8 + 4] * al); o[c * 8 + 5] = fmaf(pr, bf_hi(vv[c].z), o[c * 8 + 5] * al);
                o[c * 8 + 6] = fmaf(pr, bf_lo(vv[c].w), o[c * 8 + 6] * al); o[c * 8 + 7] = fmaf(pr, bf_hi(vv[c].w), o[c * 8 + 7] * al);
            }
        }
        CKS(3);
        if (tid == 0) TS(4);
        const uint32_t tag = *s_tag;
        if (bid >= NF) {
            const int rb = bid - NF;
            if (rb < NR) {
                float* s_rd = s_wp;
#pragma unroll 1
                for (int pass = first_pass(); pass < 2; pass++) {
                float hres = 0.f;
                if (warp == 0) {
                    uint4 a[NC];
                    mb_poll(a, g_h2 + (bid % NCOPY) * (NC * D) + rb * 32 + (lane & 7) * 4, D, tag, pass);
                    const int k = lane >> 3;
                    const float at = k == 0 ? F4SUM(a, x) : k == 1 ? F4SUM(a, y) : k == 2 ? F4SUM(a, z) : F4SUM(a, w);
                    hres = bfr(s_x[rb * 32 + (lane & 7) * 4 + k] + bfr(at));
                }
                uint4 a[3];
                mb_poll(a, g_h3 + (rb * NF + (tid >> 3)) * 32 + (tid & 7) * 4, 32 * 32, tag, pass);
                __syncwarp();
                CKS(13);
                const float s0 = __uint_as_float(a[0].x) + __uint_as_float(a[1].x) + __uint_as_float(a[2].x);
                const float s1 = __uint_as_float(a[0].y) + __uint_as_float(a[1].y) + __uint_as_float(a[2].y);
                const float s2 = __uint_as_float(a[0].z) + __uint_as_float(a[1].z) + __uint_as_float(a[2].z);
                const float s3 = __uint_as_float(a[0].w) + __uint_as_float(a[1].w) + __uint_as_float(a[2].w);
                const bool u1 = lane & 16, u2 = lane & 8;
                const float t0 = (u1 ? s2 : s0) + __shfl_xor_sync(0xffffffffu, u1 ? s0 : s2, 16);
                const float t1 = (u1 ? s3 : s1) + __shfl_xor_sync(0xffffffffu, u1 ? s1 : s3, 16);
                s_rd[warp * 32 + lane] = (u2 ? t1 : t0) + __shfl_xor_sync(0xffffffffu, u2 ? t0 : t1, 8);
                cbar();
                if (warp == 0) {
                    const float* sr = s_rd + lane;
                    const float s = ((sr[0] + sr[32]) + (sr[64] + sr[96])) + ((sr[128] + sr[160]) + (sr[192] + sr[224]));
                    const __nv_bfloat16 res = __float2bfloat16_rn(hres + bfr(s));
                    if (pass) p.out[rb * 32 + (lane & 7) * 4 + (lane >> 3)] = res;
                }
                }
                if (rb == 0 && tid == 0) mb_st(&g_epoch, tag);
                CKS(14);
                if (tid == 0) TS(7);
            }
            CKDUMP();
            return;
        }

        const int g8 = lane >> 2, c4 = lane & 3;
        uint4 ag[5], au[5], ad[5];
#pragma unroll 1
        for (int pass = first_pass(); pass < 2; pass++) {
        if (pass) mbar_wait(bar_ffn, 0);
        {
            const int mj = lane >> 3, mr = lane & 7;
#pragma unroll
            for (int s = 0; s < 5; s++) {
                const int row = warp * 80 + s * 16 + (mj >> 1) * 8 + mr;
                const uint32_t off = row * 32 + (((mj & 1) ^ ((row >> 2) & 1)) << 4);
                ag[s] = ldsm4t(sbase + SM_W + off);
                au[s] = ldsm4t(sbase + SM_WU + off);
                ad[s] = ldsm4t(sbase + SM_WD + ((mj >> 1) * 8 + mr) * ROWP + (warp * 10 + 2 * s + (mj & 1)) * 16);
            }
        }
        CKS(4);
        float* s_h = s_xn;
        float* s_st = s_wp;
        float* s_gu = s_wp + 64;
        float* s_tr = s_wp + 704;
        if (tid < 160) {
            uint4 a[NC];
            const float4 xx = reinterpret_cast<const float4*>(s_x)[tid];
            mb_poll(a, g_h2 + (bid % NCOPY) * (NC * D) + tid * 4, D, tag, pass);
            CKS(5);
            const uint32_t t0 = pack_bf2(F4SUM(a, x), F4SUM(a, y)), t1 = pack_bf2(F4SUM(a, z), F4SUM(a, w));
            const uint32_t h0 = pack_bf2(xx.x + bf_lo(t0), xx.y + bf_hi(t0)), h1 = pack_bf2(xx.z + bf_lo(t1), xx.w + bf_hi(t1));
            const float4 hh = make_float4(bf_lo(h0), bf_hi(h0), bf_lo(h1), bf_hi(h1));
            reinterpret_cast<float4*>(s_h)[tid] = hh;
            __syncwarp();
            const float s0 = __shfl_sync(0xffffffffu, hh.x, 0);
            const float a0 = hh.x - s0, a1 = hh.y - s0, a2 = hh.z - s0, a3 = hh.w - s0;
            float s1 = (a0 + a1) + (a2 + a3), s2 = (a0 * a0 + a1 * a1) + (a2 * a2 + a3 * a3);
#pragma unroll
            for (int of = 16; of > 0; of >>= 1) {
                s1 += __shfl_xor_sync(0xffffffffu, s1, of);
                s2 += __shfl_xor_sync(0xffffffffu, s2, of);
            }
            if (lane == 0) reinterpret_cast<float2*>(s_st)[warp] = make_float2(s0 + s1 * (1.0f / 128), s2 - s1 * s1 * (1.0f / 128));
        }
        CKS(6);
        cbar();
        if (tid == 0) TS(5);
        {
            const float4 p01 = reinterpret_cast<const float4*>(s_st)[0], p23 = reinterpret_cast<const float4*>(s_st)[1];
            const float2 p4 = reinterpret_cast<const float2*>(s_st)[4];
            const float2 h0 = reinterpret_cast<const float2*>(s_h)[warp * 40 + lane];
            const float2 h1 = reinterpret_cast<const float2*>(s_h)[warp * 40 + 32 + (lane & 7)];
            const float mean = ((p01.x + p01.z) + (p23.x + p23.z) + p4.x) * 0.2f;
            const float e0 = p01.x - mean, e1 = p01.z - mean, e2 = p23.x - mean, e3 = p23.z - mean, e4 = p4.x - mean;
            const float m2 = ((p01.y + p01.w) + (p23.y + p23.w) + p4.y) + 128.f * ((e0 * e0 + e1 * e1) + (e2 * e2 + e3 * e3) + e4 * e4);
            float mb, rden;
            ln_finish(mean, m2 * (1.0f / D), mb, rden);
            const uint32_t c0 = pack_bf2(h0.x - mb, h0.y - mb), c1 = pack_bf2(h1.x - mb, h1.y - mb);
            const uint32_t p0 = pack_bf2(bf_lo(c0) * rden, bf_hi(c0) * rden), p1 = pack_bf2(bf_lo(c1) * rden, bf_hi(c1) * rden);
            CKS(8);
            float dg[4] = {0.f, 0.f, 0.f, 0.f}, du[4] = {0.f, 0.f, 0.f, 0.f};
#pragma unroll
            for (int s = 0; s < 5; s++) {
                const uint32_t b0 = __shfl_sync(0xffffffffu, s < 4 ? p0 : p1, (s & 3) * 8 + c4);
                const uint32_t b1 = __shfl_sync(0xffffffffu, s < 4 ? p0 : p1, (s & 3) * 8 + 4 + c4);
                mma16816(dg, ag[s], b0, b1);
                mma16816(du, au[s], b0, b1);
            }
            if (c4 < 2) {
                s_gu[warp * 32 + c4 * 16 + g8] = c4 ? du[0] : dg[0];
                s_gu[warp * 32 + c4 * 16 + g8 + 8] = c4 ? du[2] : dg[2];
            }
            CKS(9);
            cbar();
            float s;
            {
                const float* sg = s_gu + lane;
                s = ((sg[0] + sg[32]) + (sg[64] + sg[96])) + ((sg[128] + sg[160]) + (sg[192] + sg[224]));
            }
            s = bfr(s);
            const float up = __shfl_down_sync(0xffffffffu, s, 16);
            const float act = bfr(s * rcp(1.0f + ex2(-1.4426950408889634f * s))) * up;
            const uint32_t b0 = pack_bf2(__shfl_sync(0xffffffffu, act, 2 * c4), __shfl_sync(0xffffffffu, act, 2 * c4 + 1));
            const uint32_t b1 = pack_bf2(__shfl_sync(0xffffffffu, act, 2 * c4 + 8), __shfl_sync(0xffffffffu, act, 2 * c4 + 9));
            CKS(11);
            float dd[5][4];
#pragma unroll
            for (int t = 0; t < 5; t++) {
                dd[t][0] = dd[t][1] = dd[t][2] = dd[t][3] = 0.f;
                mma16816(dd[t], ad[t], b0, b1);
            }
            const uint4 v = tiles_to_rows(dd, s_tr + warp * 80, lane, tag);
            const int col = warp * 80 + lane * 4;
            if (lane < 20 && pass) mb_st4(g_h3 + ((col >> 5) * NF + bid) * 32 + (col & 31), v);
            __syncwarp();
        }
        }
        CKS(12);
        if (tid == 0) TS(6);
        CKDUMP();
        return;
    }

    const int cj = bid - G;
    {
        const int c4 = lane & 3, cv = lane & 15, cg = warp * 2 + (lane >> 4);
        const int mj = lane >> 3, mr = lane & 7;
        mbar_wait(bar_q0, 0);
        const uint32_t tag = *s_tag;
        float acc[5][4];
#pragma unroll
        for (int t = 0; t < 5; t++) acc[t][0] = acc[t][1] = acc[t][2] = acc[t][3] = 0.f;
        int st = 0;
        uint32_t ph = 0;
#pragma unroll 1
        for (int h = 0; h < H; h++) {
            uint4 aw[5][3];
            mbar_wait(bar_full + 8 * st, ph);
#pragma unroll
            for (int t = 0; t < 5; t++)
#pragma unroll
                for (int s = 0; s < 3; s++)
                    aw[t][s] = ldsm4t(sbase + SM_RING + st * WO_BYTES + (s * 16 + (mj >> 1) * 8 + mr) * ROWP + (warp * 10 + 2 * t + (mj & 1)) * 16);
            __syncwarp();
            if (lane == 0) mbar_arrive(bar_empty + 8 * st);
            if (++st == WO_ST) { st = 0; ph ^= 1; }

            uint32_t* slot = g_part + (((h % RD) * NC + cj) * G + cg) * SLOT_P + cv * 4;
#pragma unroll 1
            for (int pass = first_pass(); pass < 2; pass++) {
            uint4 a[8];
            if (h < H - 1 && pass) {
                unsigned it = 0;
                while (!(mb_ld(slot) & 1u) && cv < 13) { __nanosleep(300); if (++it > SPIN_LIMIT) __trap(); }
            }
            mb_poll(a, slot, 16 * SLOT_P, 1u, cv < 13 && pass);
            __syncwarp();
            CKS(0);
            float mi[8];
#pragma unroll
            for (int i = 0; i < 8; i++) mi[i] = __uint_as_float(__shfl_sync(0xffffffffu, a[i].y, (lane & 16) | 12));
            float mt = fmaxf(fmaxf(fmaxf(mi[0], mi[1]), fmaxf(mi[2], mi[3])), fmaxf(fmaxf(mi[4], mi[5]), fmaxf(mi[6], mi[7])));
            mt = fmaxf(mt, __shfl_xor_sync(0xffffffffu, mt, 16));
            float4 sa = make_float4(0.f, 0.f, 0.f, 0.f), sb = sa;
#pragma unroll
            for (int i = 0; i < 8; i += 2) {
                const float w = ex2(mi[i] - mt), w2 = ex2(mi[i + 1] - mt);
                sa.x = fmaf(w, __uint_as_float(a[i].x), sa.x); sa.y = fmaf(w, __uint_as_float(a[i].y), sa.y);
                sa.z = fmaf(w, __uint_as_float(a[i].z), sa.z); sa.w = fmaf(w, __uint_as_float(a[i].w), sa.w);
                sb.x = fmaf(w2, __uint_as_float(a[i + 1].x), sb.x); sb.y = fmaf(w2, __uint_as_float(a[i + 1].y), sb.y);
                sb.z = fmaf(w2, __uint_as_float(a[i + 1].z), sb.z); sb.w = fmaf(w2, __uint_as_float(a[i + 1].w), sb.w);
            }
            sa.x += sb.x; sa.y += sb.y; sa.z += sb.z; sa.w += sb.w;
            sa.x += __shfl_xor_sync(0xffffffffu, sa.x, 16); sa.y += __shfl_xor_sync(0xffffffffu, sa.y, 16);
            sa.z += __shfl_xor_sync(0xffffffffu, sa.z, 16); sa.w += __shfl_xor_sync(0xffffffffu, sa.w, 16);
            float* cp = s_wp + (h & 1) * 512;
            if (lane < 13) reinterpret_cast<float4*>(cp + warp * 52)[lane] = sa;
            if (lane == 0) cp[448 + warp] = mt;
            CKS(1);
            cbar();
            {
                const float4 m0 = reinterpret_cast<const float4*>(cp + 448)[0], m1 = reinterpret_cast<const float4*>(cp + 448)[1];
                const float mw[8] = {m0.x, m0.y, m0.z, m0.w, m1.x, m1.y, m1.z, m1.w};
                const float M = fmaxf(fmaxf(fmaxf(mw[0], mw[1]), fmaxf(mw[2], mw[3])), fmaxf(fmaxf(mw[4], mw[5]), fmaxf(mw[6], mw[7])));
                const int pi = lane < 24 ? lane : 24;
                float n0 = 0.f, n1 = 0.f, n2 = 0.f, n3 = 0.f;
#pragma unroll
                for (int w = 0; w < 8; w += 2) {
                    const float e = ex2(mw[w] - M), e2 = ex2(mw[w + 1] - M);
                    const float2 v = reinterpret_cast<const float2*>(cp + w * 52)[pi], v2 = reinterpret_cast<const float2*>(cp + (w + 1) * 52)[pi];
                    n0 = fmaf(e, v.x, n0); n1 = fmaf(e, v.y, n1);
                    n2 = fmaf(e2, v2.x, n2); n3 = fmaf(e2, v2.y, n3);
                }
                n0 += n2; n1 += n3;
                const float rd = rcp(__shfl_sync(0xffffffffu, n0, 24));
                const uint32_t pk = pass ? pack_bf2(n0 * rd, n1 * rd) : 0u;
                CKS(3);
#pragma unroll
                for (int s = 0; s < 3; s++) {
                    const uint32_t b0 = __shfl_sync(0xffffffffu, pk, s * 8 + c4), b1 = __shfl_sync(0xffffffffu, pk, s * 8 + 4 + c4);
#pragma unroll
                    for (int t = 0; t < 5; t++) mma16816(acc[t], aw[t][s], b0, b1);
                }
            }
            CKS(4);
            {
                const uint4 v = tiles_to_rows(acc, s_wp + 1024 + warp * 80, lane, tag);
                if (h == H - 1 && lane < 20 && pass) {
#pragma unroll
                    for (int c = 0; c < NCOPY; c++) mb_st4(g_h2 + (c * NC + cj) * D + warp * 80 + lane * 4, v);
                }
                __syncwarp();
            }
            CKS(5);
            }
            if (cv < 13) {
#pragma unroll
                for (int i = 0; i < 8; i++) mb_st4(slot + i * 16 * SLOT_P, make_uint4(0u, 0u, 0u, 0u));
            }
        }
        if (tid == 0) TS(4);
        if (cj == 0 && tid == 0) mb_st(&g_ticket, 0u);
        CKDUMP();
    }
}

typedef CUresult (*EncodeFn)(CUtensorMap*, CUtensorMapDataType, cuuint32_t, void*, const cuuint64_t*, const cuuint64_t*,
                             const cuuint32_t*, const cuuint32_t*, CUtensorMapInterleave, CUtensorMapSwizzle,
                             CUtensorMapL2promotion, CUtensorMapFloatOOBfill);

void encode2d(EncodeFn fn, CUtensorMap* tm, const void* base, uint64_t d0, uint64_t d1, uint32_t b0, uint32_t b1,
              CUtensorMapSwizzle sw, CUtensorMapL2promotion promo) {
    cuuint64_t dims[2] = {d0, d1};
    cuuint64_t strides[1] = {d0 * 2};
    cuuint32_t box[2] = {b0, b1};
    cuuint32_t es[2] = {1, 1};
    fn(tm, CU_TENSOR_MAP_DATA_TYPE_BFLOAT16, 2, const_cast<void*>(base), dims, strides, box, es, CU_TENSOR_MAP_INTERLEAVE_NONE,
       sw, promo, CU_TENSOR_MAP_FLOAT_OOB_FILL_NONE);
}

}

#define CFG_PROMO CU_TENSOR_MAP_L2_PROMOTION_L2_128B

extern "C" void kernel_launch(void* const* d_in, const int* in_sizes, int n_in, void* d_out, int out_size) {
    (void)in_sizes; (void)n_in; (void)out_size;
    static EncodeFn encode = nullptr;
    if (!encode) {
        void* fn = nullptr;
        cudaDriverEntryPointQueryResult qr;
        cudaGetDriverEntryPoint("cuTensorMapEncodeTiled", &fn, cudaEnableDefault, &qr);
        encode = (EncodeFn)fn;
        cudaFuncSetAttribute(fused_decode_kernel, cudaFuncAttributeMaxDynamicSharedMemorySize, SMEM_BYTES);
    }
    Params p;
    p.x = (const __nv_bfloat16*)d_in[0];
    p.k = (const __nv_bfloat16*)d_in[1];
    p.v = (const __nv_bfloat16*)d_in[2];
    p.wq = (const __nv_bfloat16*)d_in[3];
    p.wo = (const __nv_bfloat16*)d_in[4];
    p.wd = (const __nv_bfloat16*)d_in[8];
    p.out = (__nv_bfloat16*)d_out;
    encode2d(encode, &p.tm_wq, d_in[3], HD, D, 48, 160, CU_TENSOR_MAP_SWIZZLE_NONE, CFG_PROMO);
    encode2d(encode, &p.tm_wg, d_in[6], F, D, 16, 160, CU_TENSOR_MAP_SWIZZLE_32B, CFG_PROMO);
    encode2d(encode, &p.tm_wu, d_in[7], F, D, 16, 160, CU_TENSOR_MAP_SWIZZLE_32B, CFG_PROMO);
    fused_decode_kernel<<<G + NC, NTHREADS, SMEM_BYTES, cudaStreamPerThread>>>(p);
}
```

```cpp
#include <cuda_runtime.h>
#include <cuda_bf16.h>
#include <cuda.h>
#include <stdint.h>

namespace {

constexpr int D = 640, H = 32, SK = 32768, DH = 192, F = 1536, HD = H * DH;
constexpr int TILE_KEYS = 32;
constexpr int TILE_BYTES = TILE_KEYS * DH * 2;
constexpr int STAGE_BYTES = 2 * TILE_BYTES;
constexpr int TILES_PER_HEAD = SK / TILE_KEYS;
constexpr int NTILES = H * TILES_PER_HEAD;
constexpr int NST = 3;
constexpr int NS0 = 5;
constexpr int W0 = 2;
constexpr int G = 128;
constexpr int NC = 4;
constexpr int DC = DH / NC;
constexpr int SLOT_P = 64;
constexpr int RD = 4;
constexpr int NF = 96;
constexpr int NR = 20;
constexpr int RC = D / NR;
constexpr int NQ0 = 48;
constexpr int ROWP = D * 2 + 16;
constexpr int WO_BYTES = DC * ROWP;
constexpr int WO_ST = 3;
constexpr int NTHREADS = 320;
constexpr unsigned SPIN_LIMIT = 1u << 22;

constexpr int SM_RING = 0;
constexpr int SM_W = NS0 * STAGE_BYTES;
constexpr int SM_WU = SM_W + D * 32, SM_WD = SM_W + 2 * D * 32;
constexpr int W_BYTES = 2 * D * 32 + 16 * ROWP;
constexpr int REGA = (SM_W + W_BYTES > WO_ST * WO_BYTES) ? SM_W + W_BYTES : WO_ST * WO_BYTES;
constexpr int SM_Q = (REGA + 127) / 128 * 128;
constexpr int SM_WP = SM_Q + HD * 2;
constexpr int SM_X = SM_WP + 2 * 8 * 200 * 4;
constexpr int SM_XN = SM_X + D * 4;
constexpr int SM_XP = SM_XN + D * 4;
constexpr int SM_BAR = SM_XP + D * 2;
constexpr int SMEM_BYTES = SM_BAR + 256;
constexpr int SM_W0 = SM_WP, SM_XR = SM_W0 + 160 * 32, SM_EP = SM_XR + D * 2;
static_assert(SMEM_BYTES <= 232448, "smem");
static_assert(NS0 >= WO_ST && NS0 <= 8 && SM_W % 256 == 0, "stages");

constexpr int H2P = 8 * 96;
struct Scratch {
    alignas(256) uint32_t ticket[64];
    alignas(256) uint32_t epoch[64];
    alignas(256) uint32_t q0[4 * DH];
    alignas(256) uint32_t q[HD];
    alignas(256) uint32_t part[RD * NC * G * SLOT_P];
    alignas(256) uint32_t h2[NC * H2P];
    alignas(256) uint32_t h3[NF * D];
};
__device__ Scratch g_scratch;

__device__ __forceinline__ uint32_t smem_u32(const void* p) { return (uint32_t)__cvta_generic_to_shared(p); }
__device__ __forceinline__ void mbar_init(uint32_t bar, uint32_t cnt) {
    asm volatile("mbarrier.init.shared::cta.b64 [%0], %1;" ::"r"(bar), "r"(cnt) : "memory");
}
__device__ __forceinline__ void mbar_expect_tx(uint32_t bar, uint32_t bytes) {
    asm volatile("mbarrier.arrive.expect_tx.shared::cta.b64 _, [%0], %1;" ::"r"(bar), "r"(bytes) : "memory");
}
__device__ __forceinline__ void mbar_arrive(uint32_t bar) {
    asm volatile("mbarrier.arrive.shared::cta.b64 _, [%0];" ::"r"(bar) : "memory");
}
__device__ __forceinline__ void mbar_wait(uint32_t bar, uint32_t parity) {
    uint32_t done;
    unsigned it = 0;
    while (true) {
        asm volatile("{\n.reg .pred p;\nmbarrier.try_wait.parity.shared::cta.b64 p, [%1], %2;\nselp.u32 %0, 1, 0, p;\n}"
                     : "=r"(done) : "r"(bar), "r"(parity) : "memory");
        if (done) break;
        if (++it > SPIN_LIMIT) __trap();
    }
}
__device__ __forceinline__ void bulk_load(uint32_t dst, const void* src, uint32_t bytes, uint32_t bar, uint64_t pol) {
    asm volatile("cp.async.bulk.shared::cluster.global.mbarrier::complete_tx::bytes.L2::cache_hint [%0], [%1], %2, [%3], %4;"
                 ::"r"(dst), "l"(src), "r"(bytes), "r"(bar), "l"(pol) : "memory");
}
__device__ __forceinline__ void tensor_load2d(uint32_t dst, const CUtensorMap* tm, int c0, int c1, uint32_t bar, uint64_t pol) {
    asm volatile("cp.async.bulk.tensor.2d.shared::cluster.global.mbarrier::complete_tx::bytes.L2::cache_hint [%0], [%1, {%2, %3}], [%4], %5;"
                 ::"r"(dst), "l"(tm), "r"(c0), "r"(c1), "r"(bar), "l"(pol) : "memory");
}
__device__ __forceinline__ void cbar() { asm volatile("bar.sync 1, 256;" ::: "memory"); }

__device__ __forceinline__ uint4 mb_ld4(const uint32_t* p) {
    uint4 v;
    asm volatile("ld.relaxed.gpu.global.v4.u32 {%0,%1,%2,%3}, [%4];" : "=r"(v.x), "=r"(v.y), "=r"(v.z), "=r"(v.w) : "l"(p) : "memory");
    return v;
}
__device__ __forceinline__ uint32_t mb_ld(const uint32_t* p) {
    uint32_t v;
    asm volatile("ld.relaxed.gpu.global.u32 %0, [%1];" : "=r"(v) : "l"(p) : "memory");
    return v;
}
__device__ __forceinline__ void mb_st4(uint32_t* p, uint4 v) {
    asm volatile("st.relaxed.gpu.global.v4.u32 [%0], {%1,%2,%3,%4};" ::"l"(p), "r"(v.x), "r"(v.y), "r"(v.z), "r"(v.w) : "memory");
}
__device__ __forceinline__ void mb_st(uint32_t* p, uint32_t v) {
    asm volatile("st.relaxed.gpu.global.u32 [%0], %1;" ::"l"(p), "r"(v) : "memory");
}
__device__ __forceinline__ uint32_t mb_enc(float f, uint32_t tag) { return (__float_as_uint(f) & ~1u) | tag; }
__device__ __forceinline__ uint32_t mb_miss(uint4 v, uint32_t tag) { return ((v.x ^ tag) | (v.y ^ tag) | (v.z ^ tag) | (v.w ^ tag)) & 1u; }
__device__ __forceinline__ void mb_ld4_if(uint4& a, const uint32_t* p, uint32_t pred) {
    asm volatile("{\n.reg .pred p;\nsetp.ne.u32 p, %5, 0;\n@p ld.relaxed.gpu.global.v4.u32 {%0,%1,%2,%3}, [%4];\n}"
                 : "+r"(a.x), "+r"(a.y), "+r"(a.z), "+r"(a.w) : "l"(p), "r"(pred) : "memory");
}
template <int N, bool FRESH = true>
__device__ __forceinline__ void mb_poll(uint4 (&a)[N], const uint32_t* p, int stride, uint32_t tag, bool active = true) {
    uint32_t miss[N];
#pragma unroll
    for (int i = 0; i < N; i++) {
        if (FRESH) a[i] = make_uint4(tag, tag, tag, tag);
        miss[i] = FRESH ? active : mb_miss(a[i], tag);
    }
    unsigned it = 0;
    while (true) {
#pragma unroll
        for (int i = 0; i < N; i++) mb_ld4_if(a[i], p + i * stride, miss[i]);
        uint32_t any = 0u;
#pragma unroll
        for (int i = 0; i < N; i++) {
            miss[i] = ((a[i].x ^ tag) | (a[i].y ^ tag)) | ((a[i].z ^ tag) | (a[i].w ^ tag));
            any |= miss[i];
        }
        asm volatile("" : "+r"(any));
        if (!(any & 1u)) break;
#pragma unroll
        for (int i = 0; i < N; i++) miss[i] &= 1u;
        if (++it > SPIN_LIMIT) __trap();
    }
}
#define F4SUM(v, c) ((__uint_as_float(v[0].c) + __uint_as_float(v[1].c)) + (__uint_as_float(v[2].c) + __uint_as_float(v[3].c)))

__device__ __forceinline__ float bf_lo(uint32_t w) { return __uint_as_float(w << 16); }
__device__ __forceinline__ float bf_hi(uint32_t w) { return __uint_as_float(w & 0xffff0000u); }
__device__ __forceinline__ uint32_t pack_bf2(float lo, float hi) {
    uint32_t r;
    asm("cvt.rn.bf16x2.f32 %0, %1, %2;" : "=r"(r) : "f"(hi), "f"(lo));
    return r;
}
__device__ __forceinline__ float bfr(float f) { return __uint_as_float(pack_bf2(0.f, f)); }
template <class T> __device__ __forceinline__ T* pin(T* p) { asm volatile("" : "+l"(p)); return p; }
__device__ __forceinline__ float ex2(float x) { float y; asm("ex2.approx.ftz.f32 %0, %1;" : "=f"(y) : "f"(x)); return y; }
__device__ __forceinline__ float rcp(float x) { float y; asm("rcp.approx.ftz.f32 %0, %1;" : "=f"(y) : "f"(x)); return y; }
__device__ __forceinline__ uint4 lds4(uint32_t a) {
    uint4 v;
    asm volatile("ld.shared.v4.u32 {%0,%1,%2,%3}, [%4];" : "=r"(v.x), "=r"(v.y), "=r"(v.z), "=r"(v.w) : "r"(a) : "memory");
    return v;
}
__device__ __forceinline__ uint2 lds2(uint32_t a) {
    uint2 v;
    asm volatile("ld.shared.v2.u32 {%0,%1}, [%2];" : "=r"(v.x), "=r"(v.y) : "r"(a) : "memory");
    return v;
}
__device__ __forceinline__ uint32_t lds1(uint32_t a) {
    uint32_t v;
    asm volatile("ld.shared.u32 %0, [%1];" : "=r"(v) : "r"(a) : "memory");
    return v;
}
__device__ __forceinline__ uint4 ldsm4t(uint32_t a) {
    uint4 v;
    asm volatile("ldmatrix.sync.aligned.m8n8.x4.trans.shared.b16 {%0,%1,%2,%3}, [%4];" : "=r"(v.x), "=r"(v.y), "=r"(v.z), "=r"(v.w) : "r"(a) : "memory");
    return v;
}
__device__ __forceinline__ void mma16816(float* d, uint4 a, uint32_t b0, uint32_t b1) {
    asm volatile("mma.sync.aligned.m16n8k16.row.col.f32.bf16.bf16.f32 {%0,%1,%2,%3}, {%4,%5,%6,%7}, {%8,%9}, {%0,%1,%2,%3};"
                 : "+f"(d[0]), "+f"(d[1]), "+f"(d[2]), "+f"(d[3]) : "r"(a.x), "r"(a.y), "r"(a.z), "r"(a.w), "r"(b0), "r"(b1));
}
__device__ __forceinline__ void fma8(float* acc, float s, uint4 w) {
    acc[0] = fmaf(s, bf_lo(w.x), acc[0]); acc[1] = fmaf(s, bf_hi(w.x), acc[1]);
    acc[2] = fmaf(s, bf_lo(w.y), acc[2]); acc[3] = fmaf(s, bf_hi(w.y), acc[3]);
    acc[4] = fmaf(s, bf_lo(w.z), acc[4]); acc[5] = fmaf(s, bf_hi(w.z), acc[5]);
    acc[6] = fmaf(s, bf_lo(w.w), acc[6]); acc[7] = fmaf(s, bf_hi(w.w), acc[7]);
}
__device__ __forceinline__ void ln_finish(float mean, float var, float& mean_b, float& rden) {
    mean_b = bfr(mean);
    float sq;
    asm("sqrt.approx.ftz.f32 %0, %1;" : "=f"(sq) : "f"(bfr(bfr(fmaxf(var, 0.f)) + 1e-5f)));
    rden = rcp(bfr(sq));
}
__device__ __forceinline__ float sel4(bool b0, bool b1, float v0, float v1, float v2, float v3) {
    float lo, hi, r;
    asm("{\n.reg .pred p;\nsetp.ne.u32 p, %3, 0;\nselp.f32 %0, %2, %1, p;\n}" : "=f"(lo) : "f"(v0), "f"(v1), "r"((uint32_t)b0));
    asm("{\n.reg .pred p;\nsetp.ne.u32 p, %3, 0;\nselp.f32 %0, %2, %1, p;\n}" : "=f"(hi) : "f"(v2), "f"(v3), "r"((uint32_t)b0));
    asm("{\n.reg .pred p;\nsetp.ne.u32 p, %3, 0;\nselp.f32 %0, %2, %1, p;\n}" : "=f"(r) : "f"(lo), "f"(hi), "r"((uint32_t)b1));
    return r;
}
__device__ __forceinline__ void sts2(uint32_t a, float v0, float v1) {
    asm volatile("st.shared.v2.f32 [%0], {%1,%2};" ::"r"(a), "f"(v0), "f"(v1) : "memory");
}
__device__ __forceinline__ void mb_st2(uint32_t* p, uint32_t a, uint32_t b) {
    asm volatile("st.relaxed.gpu.global.v2.u32 [%0], {%1,%2};" ::"l"(p), "r"(a), "r"(b) : "memory");
}
__device__ __forceinline__ void send_tiles(const float (&d)[5][4], uint32_t* p03, uint32_t* p4, int lane, uint32_t tag) {
    const bool b0 = lane & 1, b1 = lane & 2;
    mb_st2(p03, mb_enc(sel4(b0, b1, d[0][0], d[1][0], d[2][0], d[3][0]), tag), mb_enc(sel4(b0, b1, d[0][2], d[1][2], d[2][2], d[3][2]), tag));
    if ((lane & 3) == 0) mb_st2(p4, mb_enc(d[4][0], tag), mb_enc(d[4][2], tag));
}

struct Ptrs {
    const __nv_bfloat16 *k, *v, *x;
    Scratch* sc;
    const __nv_bfloat16 *wo, *wd;
    __nv_bfloat16* out;
};
struct alignas(64) Maps { CUtensorMap w0, wq, wg, wu; };

__global__ void __launch_bounds__(NTHREADS, 1) fused_decode_kernel(const Ptrs p, const __grid_constant__ Maps tm) {
    extern __shared__ __align__(1024) unsigned char smem[];
    const int tid = threadIdx.x, warp = tid >> 5, lane = tid & 31, bid = blockIdx.x;
    const uint32_t sbase = smem_u32(smem);
    const uint32_t bar_full = sbase + SM_BAR, bar_empty = sbase + SM_BAR + 64;
    const uint32_t bar_wq = sbase + SM_BAR + 192, bar_x = bar_wq + 16, bar_q0 = bar_wq + 24, bar_ffn = bar_wq + 32;
    volatile int* s_tile = reinterpret_cast<volatile int*>(smem + SM_BAR + 128);
    volatile int* s_qready = s_tile + 8;
    volatile uint32_t* s_tag = reinterpret_cast<volatile uint32_t*>(s_tile + 9);
    float* s_wp = reinterpret_cast<float*>(smem + SM_WP);
    float* s_x = reinterpret_cast<float*>(smem + SM_X);
    float* s_xn = reinterpret_cast<float*>(smem + SM_XN);
    uint32_t* const g_ticket = p.sc->ticket;
    uint32_t* const g_epoch = p.sc->epoch;
    uint32_t* const g_q0 = p.sc->q0;
    uint32_t* const g_q = p.sc->q;
    uint32_t* const g_part = p.sc->part;
    uint32_t* const g_h2 = p.sc->h2;
    uint32_t* const g_h3 = p.sc->h3;
    const bool streaming = bid < G;
    const char* kb = reinterpret_cast<const char*>(p.k);
    const char* vb = reinterpret_cast<const char*>(p.v);
    uint64_t pol = 0;
    auto startup_bar = [&](int i) { return i < 2 ? bar_full + 8 * i : i < 4 ? bar_wq + 8 * (i - 2) : bar_full + 8 * (i - 2); };
    auto startup_item = [&](int i) {
        if (i == 2 || i == 3) {
            mbar_expect_tx(startup_bar(i), 320 * 96);
#pragma unroll
            for (int r = 2 * (i - 2); r < 2 * (i - 2) + 2; r++)
                tensor_load2d(sbase + SM_W + r * 160 * 96, &tm.wq, bid * 48, r * 160, startup_bar(i), pol);
        } else {
            const int sg = i < 2 ? i : i - 2;
            const unsigned t = sg * G + bid;
            s_tile[sg] = (int)t;
            mbar_expect_tx(startup_bar(i), STAGE_BYTES);
            bulk_load(sbase + SM_RING + sg * STAGE_BYTES, kb + (size_t)t * TILE_BYTES, TILE_BYTES, startup_bar(i), pol);
            bulk_load(sbase + SM_RING + sg * STAGE_BYTES + TILE_BYTES, vb + (size_t)t * TILE_BYTES, TILE_BYTES, startup_bar(i), pol);
        }
    };
    if (tid == 256) {
        asm volatile("createpolicy.fractional.L2::evict_first.b64 %0, 1.0;" : "=l"(pol));
#pragma unroll
        for (int i = 0; i < W0; i++) mbar_init(bar_full + 8 * i, 1);
        mbar_init(bar_x, 1);
        if (streaming) {
#pragma unroll
            for (int i = 0; i < W0; i++) startup_item(i);
        }
        mbar_expect_tx(bar_x, 16 + D * 2 + (bid < NQ0 ? 160 * 32 : 0));
        bulk_load(sbase + SM_XR, p.x, D * 2, bar_x, pol);
        bulk_load(sbase + SM_EP, g_epoch, 16, bar_x, pol);
        if (bid < NQ0) tensor_load2d(sbase + SM_W0, &tm.w0, (bid % 12) * 16, (bid / 12) * 160, bar_x, pol);
    }
    if (warp == 8) {
        if (lane == 0) {
#pragma unroll
            for (int i = W0; i < NS0; i++) mbar_init(bar_full + 8 * i, 1);
#pragma unroll
            for (int i = 0; i < NS0; i++) mbar_init(bar_empty + 8 * i, 8);
#pragma unroll
            for (int i = 0; i < 2; i++) mbar_init(bar_wq + 8 * i, 1);
#pragma unroll
            for (int i = 0; i < 3; i++) mbar_init(bar_ffn + 8 * i, 1);
            mbar_init(bar_q0, 1);
            *s_qready = 0;
            asm volatile("fence.proxy.async.shared::cta;" ::: "memory");
        }
        __syncwarp();
        asm volatile("bar.arrive 2, %0;" ::"n"(NTHREADS) : "memory");
        if (lane != 0) return;
        if (streaming) {
            unsigned nxt;
            asm volatile("atom.relaxed.gpu.global.add.u32 %0, [%1], 1;" : "=r"(nxt) : "l"(g_ticket) : "memory");
#pragma unroll
            for (int i = W0; i < NS0 + 2; i++) {
                mbar_wait(startup_bar(i - W0), 0);
                startup_item(i);
            }
            int st = 0;
            uint32_t ph = 0;
            while (true) {
                mbar_wait(bar_empty + 8 * st, ph);
                const unsigned t = NS0 * G + nxt;
                if (t >= NTILES) break;
                asm volatile("atom.relaxed.gpu.global.add.u32 %0, [%1], 1;" : "=r"(nxt) : "l"(g_ticket) : "memory");
                s_tile[st] = (int)t;
                mbar_expect_tx(bar_full + 8 * st, STAGE_BYTES);
                const uint32_t dst = sbase + SM_RING + st * STAGE_BYTES;
                bulk_load(dst, kb + (size_t)t * TILE_BYTES, TILE_BYTES, bar_full + 8 * st, pol);
                bulk_load(dst + TILE_BYTES, vb + (size_t)t * TILE_BYTES, TILE_BYTES, bar_full + 8 * st, pol);
                if (++st == NST) { st = 0; ph ^= 1; }
            }
            s_tile[st] = NTILES;
            mbar_arrive(bar_full + 8 * st);
            if (bid < NF) {
                unsigned it = 0;
                while (*s_qready < H) { if (++it > SPIN_LIMIT) __trap(); }
                mbar_wait(bar_full + 8 * (st == 0 ? NST - 1 : st - 1), st == 0 ? ph : ph ^ 1);
#pragma unroll 1
                for (int c = 0; c < 2; c++) {
                    mbar_expect_tx(bar_ffn + 8 * c, 2 * 320 * 32);
#pragma unroll
                    for (int r = 2 * c; r < 2 * c + 2; r++) tensor_load2d(sbase + SM_W + r * 160 * 32, &tm.wg, bid * 16, r * 160, bar_ffn + 8 * c, pol);
#pragma unroll
                    for (int r = 2 * c; r < 2 * c + 2; r++) tensor_load2d(sbase + SM_WU + r * 160 * 32, &tm.wu, bid * 16, r * 160, bar_ffn + 8 * c, pol);
                }
                mbar_wait(bar_ffn, 0);
                mbar_expect_tx(bar_ffn + 16, 16 * D * 2);
#pragma unroll 1
                for (int r = 0; r < 16; r++)
                    bulk_load(sbase + SM_WD + r * ROWP, p.wd + (size_t)(bid * 16 + r) * D, D * 2, bar_ffn + 16, pol);
            }
        } else {
            int st = 0;
            uint32_t ph = 1;
            for (int h = 0; h < H; h++) {
                if (h >= WO_ST) mbar_wait(bar_empty + 8 * st, ph);
                mbar_expect_tx(bar_full + 8 * st, DC * D * 2);
#pragma unroll 1
                for (int r = 0; r < DC; r++)
                    bulk_load(sbase + SM_RING + st * WO_BYTES + r * ROWP, p.wo + (size_t)(h * DH + (bid - G) * DC + r) * D, D * 2,
                              bar_full + 8 * st, pol);
                if (++st == WO_ST) { st = 0; ph ^= 1; }
            }
        }
        return;
    }
    if (warp == 9) {
        asm volatile("bar.sync 2, %0;" ::"n"(NTHREADS) : "memory");
        mbar_wait(bar_x, 0);
        const uint32_t tag = (lds1(sbase + SM_EP) & 1u) ^ 1u;
        uint2 xraw[5];
#pragma unroll
        for (int i = 0; i < 5; i++) xraw[i] = lds2(sbase + SM_XR + (i * 32 + lane) * 8);
        if (lane == 0) *s_tag = tag;
        if (!streaming) {
            __syncwarp();
            if (lane == 0) mbar_arrive(bar_q0);
            return;
        }
        uint32_t* s_xp = reinterpret_cast<uint32_t*>(smem + SM_XP);
        uint2* s_q = reinterpret_cast<uint2*>(smem + SM_Q);
        {
            float4 xv[5];
#pragma unroll
            for (int i = 0; i < 5; i++) xv[i] = make_float4(bf_lo(xraw[i].x), bf_hi(xraw[i].x), bf_lo(xraw[i].y), bf_hi(xraw[i].y));
            const float s0 = __shfl_sync(0xffffffffu, xv[0].x, 0);
            float s1 = 0.f, s2 = 0.f;
#pragma unroll
            for (int i = 0; i < 5; i++) {
                const float a = xv[i].x - s0, b = xv[i].y - s0, c = xv[i].z - s0, d = xv[i].w - s0;
                s1 += (a + b) + (c + d);
                s2 += (a * a + b * b) + (c * c + d * d);
            }
#pragma unroll
            for (int o = 16; o > 0; o >>= 1) {
                s1 += __shfl_xor_sync(0xffffffffu, s1, o);
                s2 += __shfl_xor_sync(0xffffffffu, s2, o);
            }
            const float e1 = s1 * (1.0f / D);
            float mb, rden;
            ln_finish(s0 + e1, s2 * (1.0f / D) - e1 * e1, mb, rden);
#pragma unroll
            for (int i = 0; i < 5; i++) {
                const uint32_t lo = pack_bf2(bfr(xv[i].x - mb) * rden, bfr(xv[i].y - mb) * rden);
                const uint32_t hi = pack_bf2(bfr(xv[i].z - mb) * rden, bfr(xv[i].w - mb) * rden);
                reinterpret_cast<float4*>(s_x)[i * 32 + lane] = xv[i];
                reinterpret_cast<float4*>(s_xn)[i * 32 + lane] = make_float4(bf_lo(lo), bf_hi(lo), bf_lo(hi), bf_hi(hi));
                reinterpret_cast<uint2*>(s_xp)[i * 32 + lane] = make_uint2(lo, hi);
            }
            __syncwarp();
        }
        if (bid < NQ0) {
            float acc[8] = {0.f, 0.f, 0.f, 0.f, 0.f, 0.f, 0.f, 0.f};
#pragma unroll
            for (int i = 0; i < 10; i++) fma8(acc, s_xn[(bid / 12) * 160 + (lane >> 1) + 16 * i], lds4(sbase + SM_W0 + (i * 32 + lane) * 16));
            const bool u1 = lane & 16, u2 = lane & 8, u3 = lane & 4;
            float r4[4], r2[2];
#pragma unroll
            for (int i = 0; i < 4; i++) r4[i] = (u1 ? acc[i + 4] : acc[i]) + __shfl_xor_sync(0xffffffffu, u1 ? acc[i] : acc[i + 4], 16);
#pragma unroll
            for (int i = 0; i < 2; i++) r2[i] = (u2 ? r4[i + 2] : r4[i]) + __shfl_xor_sync(0xffffffffu, u2 ? r4[i] : r4[i + 2], 8);
            float r1 = (u3 ? r2[1] : r2[0]) + __shfl_xor_sync(0xffffffffu, u3 ? r2[0] : r2[1], 4);
            r1 += __shfl_xor_sync(0xffffffffu, r1, 2);
            if (!(lane & 2))
                mb_st(&g_q0[(bid / 12) * DH + (bid % 12) * 16 + (lane & 1) * 8 + (u1 ? 4 : 0) + (u2 ? 2 : 0) + (u3 ? 1 : 0)], mb_enc(r1, tag));
        }
        {
            uint4 a[8];
            uint32_t miss[8];
#pragma unroll
            for (int i = 0; i < 8; i++) { a[i] = make_uint4(0u, 0u, 0u, 0u); miss[i] = 1u; }
            unsigned it = 0;
            while (true) {
#pragma unroll
                for (int i = 0; i < 8; i++) mb_ld4_if(a[i], g_q0 + (i < 4 ? lane * 4 : 128 + (lane & 15) * 4) + (i & 3) * DH, miss[i]);
                uint32_t any = 0u;
#pragma unroll
                for (int i = 0; i < 8; i++) { miss[i] &= mb_miss(a[i], tag); any |= miss[i]; }
                if (!any) break;
                if (++it > SPIN_LIMIT) __trap();
            }
            const uint4* b = a + 4;
            s_q[lane] = make_uint2(pack_bf2(F4SUM(a, x), F4SUM(a, y)), pack_bf2(F4SUM(a, z), F4SUM(a, w)));
            if (lane < 16) s_q[32 + lane] = make_uint2(pack_bf2(F4SUM(b, x), F4SUM(b, y)), pack_bf2(F4SUM(b, z), F4SUM(b, w)));
            __syncwarp();
            if (lane == 0) mbar_arrive(bar_q0);
        }
        mbar_wait(bar_wq, 0);
        mbar_wait(bar_wq + 8, 0);
        {
            const int g8 = lane >> 2, c4 = lane & 3, mj = lane >> 3, mr = lane & 7;
            float dq[3][4];
#pragma unroll
            for (int t = 0; t < 3; t++) dq[t][0] = dq[t][1] = dq[t][2] = dq[t][3] = 0.f;
            const uint32_t a0 = sbase + SM_W + ((mj >> 1) * 8 + mr) * 96 + (mj & 1) * 16;
#pragma unroll 4
            for (int s = 0; s < 40; s++) {
                const uint32_t b0 = s_xp[s * 8 + c4], b1 = s_xp[s * 8 + 4 + c4];
#pragma unroll
                for (int t = 0; t < 3; t++) mma16816(dq[t], ldsm4t(a0 + s * 16 * 96 + t * 32), b0, b1);
            }
            if (c4 < 3) {
                const float v0 = c4 == 0 ? dq[0][0] : c4 == 1 ? dq[1][0] : dq[2][0];
                const float v1 = c4 == 0 ? dq[0][2] : c4 == 1 ? dq[1][2] : dq[2][2];
                mb_st(&g_q[bid * 48 + c4 * 16 + g8], mb_enc(bfr(v0), tag));
                mb_st(&g_q[bid * 48 + c4 * 16 + 8 + g8], mb_enc(bfr(v1), tag));
            }
        }
#pragma unroll 1
        for (int h0 = 1; h0 < H; h0 = (h0 + 4) & ~3) {
            uint4 a[6];
            mb_poll(a, g_q + ((h0 & ~3) * (DH / 4) + lane) * 4, 128, tag);
#pragma unroll
            for (int i = 0; i < 6; i++)
                if (h0 > 1 || i * 32 + lane >= DH / 4)
                    s_q[(h0 & ~3) * (DH / 4) + i * 32 + lane] = make_uint2((a[i].x >> 16) | (a[i].y & 0xffff0000u), (a[i].z >> 16) | (a[i].w & 0xffff0000u));
            __syncwarp();
            if (lane == 0) {
                asm volatile("fence.acq_rel.cta;" ::: "memory");
                *s_qready = (h0 + 4) & ~3;
            }
        }
        return;
    }
    asm volatile("bar.sync 2, %0;" ::"n"(NTHREADS) : "memory");

    if (streaming) {
        const int j = lane & 7;
        const uint32_t k_off = (warp * 4 + (lane >> 3)) * (DH * 2) + j * 16;
        const uint32_t v_off = TILE_BYTES + warp * 4 * (DH * 2);
        const bool mb_owner = warp < NC && lane < 14;
        uint32_t* const mb_base = g_part + (warp * G + bid) * SLOT_P + lane * 4;
        const uint32_t mb_col = (lane < 12 ? warp * DC + lane * 4 : 192) * 4;
        uint4 chk = make_uint4(0u, 0u, 0u, 0u);
        mb_ld4_if(chk, mb_base, mb_owner && lane < 13);

        float q[24], o[6];
        float m = -3.0e38f, l = 0.f;
#pragma unroll
        for (int i = 0; i < 6; i++) o[i] = 0.f;
        int head = -1;
        int st = 0, nst = NS0;
        uint32_t ph = 0;
        mbar_wait(bar_q0, 0);
        while (true) {
            mbar_wait(bar_full + 8 * st, ph);
            const int th = s_tile[st] / TILES_PER_HEAD;
            const uint32_t sa = sbase + SM_RING + st * STAGE_BYTES;
            uint4 kv[3];
            uint2 va[4];
            uint32_t vb2[4];
            if (th < H) {
#pragma unroll
                for (int c = 0; c < 3; c++) kv[c] = lds4(sa + k_off + c * 128);
#pragma unroll
                for (int i = 0; i < 4; i++) {
                    va[i] = lds2(sa + v_off + i * (DH * 2) + lane * 8);
                    vb2[i] = lds1(sa + v_off + i * (DH * 2) + 256 + lane * 4);
                }
                __syncwarp();
                if (lane == 0) mbar_arrive(bar_empty + 8 * st);
            }
            if (++st == nst) { st = 0; ph ^= 1; nst = NST; }

            if (th != head) {
                if (head < 0) head = 0;
#pragma unroll 1
                for (; head < th; head++) {
                    float* wp = s_wp + (head & 1) * 1600;
                    reinterpret_cast<float4*>(wp + warp * 196)[lane] = make_float4(o[0], o[1], o[2], o[3]);
                    reinterpret_cast<float2*>(wp + warp * 196 + 128)[lane] = make_float2(o[4], o[5]);
                    if (lane == 0) { reinterpret_cast<float4*>(wp + warp * 196)[48] = make_float4(l, 0.f, 0.f, 0.f); wp[1568 + warp] = m; }
                    cbar();
                    if (mb_owner) {
                        const uint32_t wa = sbase + SM_WP + (head & 1) * 6400;
                        const uint4 m0 = lds4(wa + 1568 * 4), m1 = lds4(wa + 1572 * 4);
                        uint4 pv[8];
#pragma unroll
                        for (int w = 0; w < 8; w++) pv[w] = lds4(wa + w * 196 * 4 + mb_col);
                        const float mw[8] = {__uint_as_float(m0.x), __uint_as_float(m0.y), __uint_as_float(m0.z), __uint_as_float(m0.w),
                                             __uint_as_float(m1.x), __uint_as_float(m1.y), __uint_as_float(m1.z), __uint_as_float(m1.w)};
                        float M8 = fmaxf(fmaxf(fmaxf(mw[0], mw[1]), fmaxf(mw[2], mw[3])), fmaxf(fmaxf(mw[4], mw[5]), fmaxf(mw[6], mw[7])));
                        M8 = __uint_as_float(mb_enc(M8, 1u));
                        float4 sa = make_float4(0.f, 0.f, 0.f, 0.f), sb = sa;
#pragma unroll
                        for (int w = 0; w < 8; w += 2) {
                            const float e = ex2(mw[w] - M8), e2 = ex2(mw[w + 1] - M8);
                            sa.x = fmaf(e, __uint_as_float(pv[w].x), sa.x); sa.y = fmaf(e, __uint_as_float(pv[w].y), sa.y);
                            sa.z = fmaf(e, __uint_as_float(pv[w].z), sa.z); sa.w = fmaf(e, __uint_as_float(pv[w].w), sa.w);
                            sb.x = fmaf(e2, __uint_as_float(pv[w + 1].x), sb.x); sb.y = fmaf(e2, __uint_as_float(pv[w + 1].y), sb.y);
                            sb.z = fmaf(e2, __uint_as_float(pv[w + 1].z), sb.z); sb.w = fmaf(e2, __uint_as_float(pv[w + 1].w), sb.w);
                        }
                        uint32_t* dst = mb_base + (head % RD) * (NC * G * SLOT_P);
                        unsigned it = 0;
                        while ((chk.x | chk.y | chk.z | chk.w) != 0u) { chk = mb_ld4(dst); if (++it > SPIN_LIMIT) __trap(); }
                        mb_st4(dst, make_uint4(mb_enc(sa.x + sb.x, 1u), mb_enc(lane < 12 ? sa.y + sb.y : M8, 1u), mb_enc(sa.z + sb.z, 1u),
                                               mb_enc(sa.w + sb.w, 1u)));
                        mb_ld4_if(chk, mb_base + ((head + 1) % RD) * (NC * G * SLOT_P), lane < 13 && head + 1 < H);
                    }
                    m = -3.0e38f; l = 0.f;
#pragma unroll
                    for (int i = 0; i < 6; i++) o[i] = 0.f;
                }
                if (th == H) break;
                if (head > 0) {
                    unsigned it = 0;
                    while (*s_qready <= head) { if (++it > SPIN_LIMIT) __trap(); }
                    asm volatile("fence.acq_rel.cta;" ::: "memory");
                }
#pragma unroll
                for (int c = 0; c < 3; c++) {
                    const uint4 u = lds4(sbase + SM_Q + head * (DH * 2) + c * 128 + j * 16);
                    q[c * 8 + 0] = bf_lo(u.x); q[c * 8 + 1] = bf_hi(u.x); q[c * 8 + 2] = bf_lo(u.y); q[c * 8 + 3] = bf_hi(u.y);
                    q[c * 8 + 4] = bf_lo(u.z); q[c * 8 + 5] = bf_hi(u.z); q[c * 8 + 6] = bf_lo(u.w); q[c * 8 + 7] = bf_hi(u.w);
                }
            }
            float d0 = 0.f, d1 = 0.f, d2 = 0.f, d3 = 0.f;
#pragma unroll
            for (int c = 0; c < 3; c++) {
                d0 = fmaf(q[c * 8 + 0], bf_lo(kv[c].x), d0); d1 = fmaf(q[c * 8 + 1], bf_hi(kv[c].x), d1);
                d2 = fmaf(q[c * 8 + 2], bf_lo(kv[c].y), d2); d3 = fmaf(q[c * 8 + 3], bf_hi(kv[c].y), d3);
                d0 = fmaf(q[c * 8 + 4], bf_lo(kv[c].z), d0); d1 = fmaf(q[c * 8 + 5], bf_hi(kv[c].z), d1);
                d2 = fmaf(q[c * 8 + 6], bf_lo(kv[c].w), d2); d3 = fmaf(q[c * 8 + 7], bf_hi(kv[c].w), d3);
            }
            float s = (d0 + d1) + (d2 + d3);
            s += __shfl_xor_sync(0xffffffffu, s, 1);
            s += __shfl_xor_sync(0xffffffffu, s, 2);
            s += __shfl_xor_sync(0xffffffffu, s, 4);
            s = bfr(bfr(s) * 0.07216878364870322f) * 1.4426950408889634f;
            float sk[4];
#pragma unroll
            for (int i = 0; i < 4; i++) sk[i] = __shfl_sync(0xffffffffu, s, i * 8);
            const float mn = fmaxf(fmaxf(m, fmaxf(sk[0], sk[1])), fmaxf(sk[2], sk[3]));
            const float al = ex2(m - mn);
            m = mn;
            l *= al;
#pragma unroll
            for (int i = 0; i < 6; i++) o[i] *= al;
#pragma unroll
            for (int i = 0; i < 4; i++) {
                const float pr = ex2(sk[i] - mn);
                l += pr;
                o[0] = fmaf(pr, bf_lo(va[i].x), o[0]); o[1] = fmaf(pr, bf_hi(va[i].x), o[1]);
                o[2] = fmaf(pr, bf_lo(va[i].y), o[2]); o[3] = fmaf(pr, bf_hi(va[i].y), o[3]);
                o[4] = fmaf(pr, bf_lo(vb2[i]), o[4]);  o[5] = fmaf(pr, bf_hi(vb2[i]), o[5]);
            }
        }
        const uint32_t tag = *s_tag;
        if (bid >= NF) {
            const int rb = bid - NF;
            if (rb < NR) {
                float* s_rd = s_wp;
                const int wd = (lane & 7) * 4 + (lane >> 3);
                const int col = rb * 32 + (wd & 16) + ((wd & 15) >> 1) + (wd & 1) * 8;
                __nv_bfloat16* const dst = pin(p.out + col);
                const uint32_t* const src3 = g_h3 + rb * NF * 32 + tid * 4;
                uint4 a[3];
#pragma unroll
                for (int i = 0; i < 3; i++) a[i] = mb_ld4(src3 + i * 1024);
                float hres = 0.f;
                if (warp == 0) {
                    uint4 b[NC];
                    const int tl = rb * 2 + ((lane >> 2) & 1);
                    mb_poll(b, g_h2 + (tl / 5) * 96 + (tl % 5) * 16 + (lane & 3) * 4, H2P, tag);
                    const int k = lane >> 3;
                    const float at = k == 0 ? F4SUM(b, x) : k == 1 ? F4SUM(b, y) : k == 2 ? F4SUM(b, z) : F4SUM(b, w);
                    hres = bfr(s_x[col] + bfr(at));
                }
                cbar();
                mb_poll<3, false>(a, src3, 1024, tag);
                __syncwarp();
                const float s0 = __uint_as_float(a[0].x) + __uint_as_float(a[1].x) + __uint_as_float(a[2].x);
                const float s1 = __uint_as_float(a[0].y) + __uint_as_float(a[1].y) + __uint_as_float(a[2].y);
                const float s2 = __uint_as_float(a[0].z) + __uint_as_float(a[1].z) + __uint_as_float(a[2].z);
                const float s3 = __uint_as_float(a[0].w) + __uint_as_float(a[1].w) + __uint_as_float(a[2].w);
                const bool u1 = lane & 16, u2 = lane & 8;
                const float t0 = (u1 ? s2 : s0) + __shfl_xor_sync(0xffffffffu, u1 ? s0 : s2, 16);
                const float t1 = (u1 ? s3 : s1) + __shfl_xor_sync(0xffffffffu, u1 ? s1 : s3, 16);
                s_rd[warp * 32 + lane] = (u2 ? t1 : t0) + __shfl_xor_sync(0xffffffffu, u2 ? t0 : t1, 8);
                cbar();
                if (warp == 0) {
                    const float* sr = s_rd + lane;
                    const float s = ((sr[0] + sr[32]) + (sr[64] + sr[96])) + ((sr[128] + sr[160]) + (sr[192] + sr[224]));
                    *reinterpret_cast<unsigned short*>(dst) = (unsigned short)pack_bf2(hres + bfr(s), 0.f);
                    if (rb == 0 && lane == 0) mb_st(g_epoch, tag);
                }
            }
            return;
        }

        const int g8 = lane >> 2, c4 = lane & 3;
        uint4 ag[5], au[5], ad[5];
        uint4 a[NC];
        const uint32_t* const src2 = g_h2 + warp * 96 + lane * 4;
#pragma unroll
        for (int c = 0; c < NC; c++) {
            a[c] = make_uint4(tag, tag, tag, tag);
            mb_ld4_if(a[c], src2 + c * H2P, lane < 20);
        }
        const int mj = lane >> 3, mr = lane & 7;
        mbar_wait(bar_ffn, 0);
        mbar_wait(bar_ffn + 8, 0);
#pragma unroll
        for (int s = 0; s < 5; s++) {
            const int row = warp * 80 + s * 16 + (mr & 6) + (mr & 1) * 8 + (mj >> 1);
            const uint32_t off = row * 32 + (((mj & 1) ^ ((row >> 2) & 1)) << 4);
            ag[s] = ldsm4t(sbase + SM_W + off);
            au[s] = ldsm4t(sbase + SM_WU + off);
        }
        {
            const int t3 = warp * 5 + c4, t4 = warp * 5 + 4;
            uint32_t* const dst3 = pin(g_h3 + ((t3 >> 1) * NF + bid) * RC + (t3 & 1) * 16 + g8 * 2);
            uint32_t* const dst4 = pin(g_h3 + ((t4 >> 1) * NF + bid) * RC + (t4 & 1) * 16 + g8 * 2);
            const uint32_t a_gu = sbase + SM_WP + 64 * 4, a_st = sbase + SM_WP;
            const float* xp = s_x + warp * 80 + (lane < 20 ? g8 * 16 + c4 * 2 : 0);
            const float4 xx = make_float4(xp[0], xp[8], xp[1], xp[9]);
            mb_poll<NC, false>(a, src2, H2P, tag);
            __syncwarp();
            const uint32_t t0 = pack_bf2(F4SUM(a, x), F4SUM(a, y)), t1 = pack_bf2(F4SUM(a, z), F4SUM(a, w));
            const uint32_t h0 = pack_bf2(xx.x + bf_lo(t0), xx.y + bf_hi(t0)), h1 = pack_bf2(xx.z + bf_lo(t1), xx.w + bf_hi(t1));
            constexpr uint32_t ONES = 0x3f803f80u;
            float dg[2][4], du[2][4], ds[2][4];
#pragma unroll
            for (int i = 0; i < 2; i++)
#pragma unroll
                for (int k = 0; k < 4; k++) dg[i][k] = du[i][k] = ds[i][k] = 0.f;
            uint32_t f0[5], f1[5];
#pragma unroll
            for (int s = 0; s < 5; s++) { f0[s] = __shfl_sync(0xffffffffu, h0, s * 4 + c4); f1[s] = __shfl_sync(0xffffffffu, h1, s * 4 + c4); }
#pragma unroll
            for (int s = 0; s < 5; s++) {
                const uint32_t b0 = g8 == 1 ? ONES : f0[s], b1 = g8 == 1 ? ONES : f1[s];
                mma16816(ds[s & 1], make_uint4(f0[s], ONES, f1[s], ONES), b0, b1);
                mma16816(dg[s & 1], ag[s], b0, b1);
                mma16816(du[s & 1], au[s], b0, b1);
            }
            if (c4 == 0) {
                const uint32_t aw = a_gu + (warp * 32 + g8) * 8;
                sts2(aw, dg[0][0] + dg[1][0], dg[0][1] + dg[1][1]);
                sts2(aw + 64, dg[0][2] + dg[1][2], dg[0][3] + dg[1][3]);
                sts2(aw + 128, du[0][0] + du[1][0], du[0][1] + du[1][1]);
                sts2(aw + 192, du[0][2] + du[1][2], du[0][3] + du[1][3]);
                if (lane == 0) sts2(a_st + warp * 8, ds[0][2] + ds[1][2], ds[0][0] + ds[1][0]);
            }
            mbar_wait(bar_ffn + 16, 0);
            cbar();
            uint4 pw[4];
#pragma unroll
            for (int i = 0; i < 4; i++) pw[i] = lds4(a_st + i * 16);
            uint2 sg[8];
#pragma unroll
            for (int w = 0; w < 8; w++) sg[w] = lds2(a_gu + (w * 32 + lane) * 8);
#pragma unroll
            for (int t = 0; t < 5; t++) ad[t] = ldsm4t(sbase + SM_WD + ((mj >> 1) * 8 + mr) * ROWP + (warp * 10 + 2 * t + (mj & 1)) * 16);
            const float mean = (F4SUM(pw, x) + F4SUM(pw, z)) * (1.0f / D);
            const float ex2m = (F4SUM(pw, y) + F4SUM(pw, w)) * (1.0f / D);
            float mb, rden;
            ln_finish(mean, fmaf(-mean, mean, ex2m), mb, rden);
            const uint2* sh = sg + 4;
            const float s = bfr(fmaf(-mb, F4SUM(sg, y) + F4SUM(sh, y), F4SUM(sg, x) + F4SUM(sh, x)) * rden);
            const float up = __shfl_down_sync(0xffffffffu, s, 16);
            const float act = bfr(s * rcp(1.0f + ex2(-1.4426950408889634f * s))) * up;
            const uint32_t c0 = pack_bf2(__shfl_sync(0xffffffffu, act, 2 * c4), __shfl_sync(0xffffffffu, act, 2 * c4 + 1));
            const uint32_t c1 = pack_bf2(__shfl_sync(0xffffffffu, act, 2 * c4 + 8), __shfl_sync(0xffffffffu, act, 2 * c4 + 9));
            float dd[5][4];
#pragma unroll
            for (int t = 0; t < 5; t++) {
                dd[t][0] = dd[t][1] = dd[t][2] = dd[t][3] = 0.f;
                mma16816(dd[t], ad[t], c0, c1);
            }
            send_tiles(dd, dst3, dst4, lane, tag);
        }
        return;
    }

    const int cj = bid - G;
    {
        const int c4 = lane & 3, cv = lane & 15, cg = warp * 2 + (lane >> 4);
        const int mj = lane >> 3, mr = lane & 7;
        mbar_wait(bar_q0, 0);
        const uint32_t tag = *s_tag;
        uint32_t* const dst2 = pin(g_h2 + cj * H2P + warp * 96 + (lane >> 2) * 2);
        float acc[5][4];
#pragma unroll
        for (int t = 0; t < 5; t++) acc[t][0] = acc[t][1] = acc[t][2] = acc[t][3] = 0.f;
        int st = 0;
        uint32_t ph = 0;
#pragma unroll 1
        for (int h = 0; h < H; h++) {
            uint4 aw[5][3];
            mbar_wait(bar_full + 8 * st, ph);
#pragma unroll
            for (int t = 0; t < 5; t++)
#pragma unroll
                for (int s = 0; s < 3; s++)
                    aw[t][s] = ldsm4t(sbase + SM_RING + st * WO_BYTES + (s * 16 + (mj >> 1) * 8 + mr) * ROWP + (warp * 10 + 2 * t + (mj & 1)) * 16);
            __syncwarp();
            if (lane == 0) mbar_arrive(bar_empty + 8 * st);
            if (++st == WO_ST) { st = 0; ph ^= 1; }

            uint32_t* slot = g_part + (((h % RD) * NC + cj) * G + cg) * SLOT_P + cv * 4;
            uint4 a[8];
            if (h < H - 1) {
                unsigned it = 0;
                while (!(mb_ld(slot) & 1u) && cv < 13) { __nanosleep(300); if (++it > SPIN_LIMIT) __trap(); }
            }
            if (h == H - 1) {
                unsigned it = 0;
                while (!__any_sync(0xffffffffu, mb_ld(slot - cv * 4 + (cv & 7) * 16 * SLOT_P) & 1u)) {
                    __nanosleep(100);
                    if (++it > SPIN_LIMIT) __trap();
                }
            }
            mb_poll(a, slot, 16 * SLOT_P, 1u, cv < 13);
            __syncwarp();
            float mi[8];
#pragma unroll
            for (int i = 0; i < 8; i++) mi[i] = __uint_as_float(__shfl_sync(0xffffffffu, a[i].y, (lane & 16) | 12));
            float mt = fmaxf(fmaxf(fmaxf(mi[0], mi[1]), fmaxf(mi[2], mi[3])), fmaxf(fmaxf(mi[4], mi[5]), fmaxf(mi[6], mi[7])));
            mt = fmaxf(mt, __shfl_xor_sync(0xffffffffu, mt, 16));
            float4 sa = make_float4(0.f, 0.f, 0.f, 0.f), sb = sa;
#pragma unroll
            for (int i = 0; i < 8; i += 2) {
                const float w = ex2(mi[i] - mt), w2 = ex2(mi[i + 1] - mt);
                sa.x = fmaf(w, __uint_as_float(a[i].x), sa.x); sa.y = fmaf(w, __uint_as_float(a[i].y), sa.y);
                sa.z = fmaf(w, __uint_as_float(a[i].z), sa.z); sa.w = fmaf(w, __uint_as_float(a[i].w), sa.w);
                sb.x = fmaf(w2, __uint_as_float(a[i + 1].x), sb.x); sb.y = fmaf(w2, __uint_as_float(a[i + 1].y), sb.y);
                sb.z = fmaf(w2, __uint_as_float(a[i + 1].z), sb.z); sb.w = fmaf(w2, __uint_as_float(a[i + 1].w), sb.w);
            }
            sa.x += sb.x; sa.y += sb.y; sa.z += sb.z; sa.w += sb.w;
            sa.x += __shfl_xor_sync(0xffffffffu, sa.x, 16); sa.y += __shfl_xor_sync(0xffffffffu, sa.y, 16);
            sa.z += __shfl_xor_sync(0xffffffffu, sa.z, 16); sa.w += __shfl_xor_sync(0xffffffffu, sa.w, 16);
            float* cp = s_wp + (h & 1) * 512;
            if (lane < 13) reinterpret_cast<float4*>(cp + warp * 52)[lane] = sa;
            if (lane == 0) cp[448 + warp] = mt;
            cbar();
            {
                const float4 m0 = reinterpret_cast<const float4*>(cp + 448)[0], m1 = reinterpret_cast<const float4*>(cp + 448)[1];
                const float mw[8] = {m0.x, m0.y, m0.z, m0.w, m1.x, m1.y, m1.z, m1.w};
                const float M = fmaxf(fmaxf(fmaxf(mw[0], mw[1]), fmaxf(mw[2], mw[3])), fmaxf(fmaxf(mw[4], mw[5]), fmaxf(mw[6], mw[7])));
                const int pi = lane < 24 ? lane : 24;
                float n0 = 0.f, n1 = 0.f, n2 = 0.f, n3 = 0.f;
#pragma unroll
                for (int w = 0; w < 8; w += 2) {
                    const float e = ex2(mw[w] - M), e2 = ex2(mw[w + 1] - M);
                    const float2 v = reinterpret_cast<const float2*>(cp + w * 52)[pi], v2 = reinterpret_cast<const float2*>(cp + (w + 1) * 52)[pi];
                    n0 = fmaf(e, v.x, n0); n1 = fmaf(e, v.y, n1);
                    n2 = fmaf(e2, v2.x, n2); n3 = fmaf(e2, v2.y, n3);
                }
                n0 += n2; n1 += n3;
                const float rd = rcp(__shfl_sync(0xffffffffu, n0, 24));
                const uint32_t pk = pack_bf2(n0 * rd, n1 * rd);
#pragma unroll
                for (int s = 0; s < 3; s++) {
                    const uint32_t b0 = __shfl_sync(0xffffffffu, pk, s * 8 + c4), b1 = __shfl_sync(0xffffffffu, pk, s * 8 + 4 + c4);
#pragma unroll
                    for (int t = 0; t < 5; t++) mma16816(acc[t], aw[t][s], b0, b1);
                }
            }
            if (h == H - 1) {
                send_tiles(acc, dst2 + c4 * 16, dst2 + 64, lane, tag);
                cbar();
            }
            if (cv < 13) {
#pragma unroll
                for (int i = 0; i < 8; i++) mb_st4(slot + i * 16 * SLOT_P, make_uint4(0u, 0u, 0u, 0u));
            }
        }
        if (cj == 0 && tid == 0) mb_st(g_ticket, 0u);
    }
}

typedef CUresult (*EncodeFn)(CUtensorMap*, CUtensorMapDataType, cuuint32_t, void*, const cuuint64_t*, const cuuint64_t*,
                             const cuuint32_t*, const cuuint32_t*, CUtensorMapInterleave, CUtensorMapSwizzle,
                             CUtensorMapL2promotion, CUtensorMapFloatOOBfill);

void encode2d(EncodeFn fn, CUtensorMap* tm, const void* base, uint64_t d0, uint64_t d1, uint32_t b0, uint32_t b1,
              CUtensorMapSwizzle sw, CUtensorMapL2promotion promo) {
    cuuint64_t dims[2] = {d0, d1};
    cuuint64_t strides[1] = {d0 * 2};
    cuuint32_t box[2] = {b0, b1};
    cuuint32_t es[2] = {1, 1};
    fn(tm, CU_TENSOR_MAP_DATA_TYPE_BFLOAT16, 2, const_cast<void*>(base), dims, strides, box, es, CU_TENSOR_MAP_INTERLEAVE_NONE,
       sw, promo, CU_TENSOR_MAP_FLOAT_OOB_FILL_NONE);
}

}

extern "C" void kernel_launch(void* const* d_in, const int* in_sizes, int n_in, void* d_out, int out_size) {
    (void)in_sizes; (void)n_in; (void)out_size;
    static EncodeFn encode = nullptr;
    static void* scratch = nullptr;
    if (!encode) {
        cudaGetSymbolAddress(&scratch, g_scratch);
        void* fn = nullptr;
        cudaDriverEntryPointQueryResult qr;
        cudaGetDriverEntryPoint("cuTensorMapEncodeTiled", &fn, cudaEnableDefault, &qr);
        encode = (EncodeFn)fn;
        cudaFuncSetAttribute(fused_decode_kernel, cudaFuncAttributeMaxDynamicSharedMemorySize, SMEM_BYTES);
    }
    Ptrs p;
    Maps tm;
    p.x = (const __nv_bfloat16*)d_in[0];
    p.k = (const __nv_bfloat16*)d_in[1];
    p.v = (const __nv_bfloat16*)d_in[2];
    p.wo = (const __nv_bfloat16*)d_in[4];
    p.wd = (const __nv_bfloat16*)d_in[8];
    p.out = (__nv_bfloat16*)d_out;
    p.sc = (Scratch*)scratch;
    encode2d(encode, &tm.wq, d_in[3], HD, D, 48, 160, CU_TENSOR_MAP_SWIZZLE_NONE, CU_TENSOR_MAP_L2_PROMOTION_L2_128B);
    encode2d(encode, &tm.w0, d_in[3], HD, D, 16, 160, CU_TENSOR_MAP_SWIZZLE_NONE, CU_TENSOR_MAP_L2_PROMOTION_NONE);
    encode2d(encode, &tm.wg, d_in[6], F, D, 16, 160, CU_TENSOR_MAP_SWIZZLE_32B, CU_TENSOR_MAP_L2_PROMOTION_L2_128B);
    encode2d(encode, &tm.wu, d_in[7], F, D, 16, 160, CU_TENSOR_MAP_SWIZZLE_32B, CU_TENSOR_MAP_L2_PROMOTION_L2_128B);
    fused_decode_kernel<<<G + NC, NTHREADS, SMEM_BYTES, cudaStreamPerThread>>>(p, tm);
}
```

```cpp
#include <cuda_runtime.h>
#include <cuda_bf16.h>
#include <cuda.h>
#include <stdint.h>

namespace {

constexpr int D = 640, H = 32, SK = 32768, DH = 192, F = 1536, HD = H * DH;
constexpr int TILE_KEYS = 32;
constexpr int TILE_BYTES = TILE_KEYS * DH * 2;
constexpr int STAGE_BYTES = 2 * TILE_BYTES;
constexpr int TILES_PER_HEAD = SK / TILE_KEYS;
constexpr int NTILES = H * TILES_PER_HEAD;
constexpr int NST = 3;
constexpr int NS0 = 5;
constexpr int W0 = 2;
constexpr int G = 128;
constexpr int NC = 4;
constexpr int DC = DH / NC;
constexpr int SLOT_P = 64;
constexpr int RD = 4;
constexpr int NF = 96;
constexpr int NR = 20;
constexpr int RC = D / NR;
constexpr int NQ0 = 48;
constexpr int ROWP = D * 2 + 16;
constexpr int WO_BYTES = DC * ROWP;
constexpr int WO_ST = 3;
constexpr int NTHREADS = 320;
constexpr unsigned SPIN_LIMIT = 1u << 22;

constexpr int SM_RING = 0;
constexpr int SM_W = NS0 * STAGE_BYTES;
constexpr int SM_WU = SM_W + D * 32, SM_WD = SM_W + 2 * D * 32;
constexpr int W_BYTES = 2 * D * 32 + 16 * ROWP;
constexpr int REGA = (SM_W + W_BYTES > WO_ST * WO_BYTES) ? SM_W + W_BYTES : WO_ST * WO_BYTES;
constexpr int SM_Q = (REGA + 127) / 128 * 128;
constexpr int SM_WP = SM_Q + HD * 2;
constexpr int SM_X = SM_WP + 2 * 8 * 200 * 4;
constexpr int SM_XN = SM_X + D * 4;
constexpr int SM_XP = SM_XN + D * 4;
constexpr int SM_BAR = SM_XP + D * 2;
constexpr int SMEM_BYTES = SM_BAR + 256;
constexpr int SM_W0 = SM_WP, SM_XR = SM_W0 + 160 * 32, SM_EP = SM_XR + D * 2;
static_assert(SMEM_BYTES <= 232448, "smem");
static_assert(NS0 >= WO_ST && NS0 <= 8 && SM_W % 256 == 0, "stages");

constexpr int H2P = 8 * 96;
struct Scratch {
    alignas(256) uint32_t ticket[64];
    alignas(256) uint32_t epoch[64];
    alignas(256) uint32_t q0[4 * DH];
    alignas(256) uint32_t q[HD];
    alignas(256) uint32_t part[RD * NC * G * SLOT_P];
    alignas(256) uint32_t h2[NC * H2P];
    alignas(256) uint32_t h3[NF * D];
};
__device__ Scratch g_scratch;

__device__ __forceinline__ uint32_t smem_u32(const void* p) { return (uint32_t)__cvta_generic_to_shared(p); }
__device__ __forceinline__ void mbar_init(uint32_t bar, uint32_t cnt) {
    asm volatile("mbarrier.init.shared::cta.b64 [%0], %1;" ::"r"(bar), "r"(cnt) : "memory");
}
__device__ __forceinline__ void mbar_expect_tx(uint32_t bar, uint32_t bytes) {
    asm volatile("mbarrier.arrive.expect_tx.shared::cta.b64 _, [%0], %1;" ::"r"(bar), "r"(bytes) : "memory");
}
__device__ __forceinline__ void mbar_arrive(uint32_t bar) {
    asm volatile("mbarrier.arrive.shared::cta.b64 _, [%0];" ::"r"(bar) : "memory");
}
__device__ __forceinline__ void mbar_wait(uint32_t bar, uint32_t parity) {
    uint32_t done;
    unsigned it = 0;
    while (true) {
        asm volatile("{\n.reg .pred p;\nmbarrier.try_wait.parity.shared::cta.b64 p, [%1], %2;\nselp.u32 %0, 1, 0, p;\n}"
                     : "=r"(done) : "r"(bar), "r"(parity) : "memory");
        if (done) break;
        if (++it > SPIN_LIMIT) __trap();
    }
}
__device__ __forceinline__ bool mbar_test(uint32_t bar, uint32_t parity) {
    uint32_t done;
    asm volatile("{\n.reg .pred p;\nmbarrier.test_wait.parity.shared::cta.b64 p, [%1], %2;\nselp.u32 %0, 1, 0, p;\n}"
                 : "=r"(done) : "r"(bar), "r"(parity) : "memory");
    return done;
}
__device__ __forceinline__ void bulk_load(uint32_t dst, const void* src, uint32_t bytes, uint32_t bar, uint64_t pol) {
    asm volatile("cp.async.bulk.shared::cluster.global.mbarrier::complete_tx::bytes.L2::cache_hint [%0], [%1], %2, [%3], %4;"
                 ::"r"(dst), "l"(src), "r"(bytes), "r"(bar), "l"(pol) : "memory");
}
__device__ __forceinline__ void tensor_load2d(uint32_t dst, const CUtensorMap* tm, int c0, int c1, uint32_t bar, uint64_t pol) {
    asm volatile("cp.async.bulk.tensor.2d.shared::cluster.global.mbarrier::complete_tx::bytes.L2::cache_hint [%0], [%1, {%2, %3}], [%4], %5;"
                 ::"r"(dst), "l"(tm), "r"(c0), "r"(c1), "r"(bar), "l"(pol) : "memory");
}
__device__ __forceinline__ void cbar() { asm volatile("bar.sync 1, 256;" ::: "memory"); }

__device__ __forceinline__ uint4 mb_ld4(const uint32_t* p) {
    uint4 v;
    asm volatile("ld.relaxed.gpu.global.v4.u32 {%0,%1,%2,%3}, [%4];" : "=r"(v.x), "=r"(v.y), "=r"(v.z), "=r"(v.w) : "l"(p) : "memory");
    return v;
}
__device__ __forceinline__ uint32_t mb_ld(const uint32_t* p) {
    uint32_t v;
    asm volatile("ld.relaxed.gpu.global.u32 %0, [%1];" : "=r"(v) : "l"(p) : "memory");
    return v;
}
__device__ __forceinline__ void mb_st4(uint32_t* p, uint4 v) {
    asm volatile("st.relaxed.gpu.global.v4.u32 [%0], {%1,%2,%3,%4};" ::"l"(p), "r"(v.x), "r"(v.y), "r"(v.z), "r"(v.w) : "memory");
}
__device__ __forceinline__ void mb_st(uint32_t* p, uint32_t v) {
    asm volatile("st.relaxed.gpu.global.u32 [%0], %1;" ::"l"(p), "r"(v) : "memory");
}
__device__ __forceinline__ uint32_t mb_enc(float f, uint32_t tag) { return (__float_as_uint(f) & ~1u) | tag; }
__device__ __forceinline__ uint32_t mb_miss(uint4 v, uint32_t tag) { return ((v.x ^ tag) | (v.y ^ tag) | (v.z ^ tag) | (v.w ^ tag)) & 1u; }
__device__ __forceinline__ void mb_ld4_if(uint4& a, const uint32_t* p, uint32_t pred) {
    asm volatile("{\n.reg .pred p;\nsetp.ne.u32 p, %5, 0;\n@p ld.relaxed.gpu.global.v4.u32 {%0,%1,%2,%3}, [%4];\n}"
                 : "+r"(a.x), "+r"(a.y), "+r"(a.z), "+r"(a.w) : "l"(p), "r"(pred) : "memory");
}
template <int N, bool FRESH = true>
__device__ __forceinline__ void mb_poll(uint4 (&a)[N], const uint32_t* p, int stride, uint32_t tag, bool active = true) {
    uint32_t miss[N];
#pragma unroll
    for (int i = 0; i < N; i++) {
        if (FRESH) a[i] = make_uint4(tag, tag, tag, tag);
        miss[i] = FRESH ? active : mb_miss(a[i], tag);
    }
    unsigned it = 0;
    while (true) {
#pragma unroll
        for (int i = 0; i < N; i++) mb_ld4_if(a[i], p + i * stride, miss[i]);
        uint32_t any = 0u;
#pragma unroll
        for (int i = 0; i < N; i++) {
            miss[i] = ((a[i].x ^ tag) | (a[i].y ^ tag)) | ((a[i].z ^ tag) | (a[i].w ^ tag));
            any |= miss[i];
        }
        asm volatile("" : "+r"(any));
        if (!(any & 1u)) break;
#pragma unroll
        for (int i = 0; i < N; i++) miss[i] &= 1u;
        if (++it > SPIN_LIMIT) __trap();
    }
}
#define F4SUM(v, c) ((__uint_as_float(v[0].c) + __uint_as_float(v[1].c)) + (__uint_as_float(v[2].c) + __uint_as_float(v[3].c)))

__device__ __forceinline__ float bf_lo(uint32_t w) { return __uint_as_float(w << 16); }
__device__ __forceinline__ float bf_hi(uint32_t w) { return __uint_as_float(w & 0xffff0000u); }
__device__ __forceinline__ uint32_t pack_bf2(float lo, float hi) {
    uint32_t r;
    asm("cvt.rn.bf16x2.f32 %0, %1, %2;" : "=r"(r) : "f"(hi), "f"(lo));
    return r;
}
__device__ __forceinline__ float bfr(float f) { return __uint_as_float(pack_bf2(0.f, f)); }
template <class T> __device__ __forceinline__ T* pin(T* p) { asm volatile("" : "+l"(p)); return p; }
__device__ __forceinline__ float ex2(float x) { float y; asm("ex2.approx.ftz.f32 %0, %1;" : "=f"(y) : "f"(x)); return y; }
__device__ __forceinline__ float rcp(float x) { float y; asm("rcp.approx.ftz.f32 %0, %1;" : "=f"(y) : "f"(x)); return y; }
__device__ __forceinline__ uint4 lds4(uint32_t a) {
    uint4 v;
    asm volatile("ld.shared.v4.u32 {%0,%1,%2,%3}, [%4];" : "=r"(v.x), "=r"(v.y), "=r"(v.z), "=r"(v.w) : "r"(a) : "memory");
    return v;
}
__device__ __forceinline__ uint2 lds2(uint32_t a) {
    uint2 v;
    asm volatile("ld.shared.v2.u32 {%0,%1}, [%2];" : "=r"(v.x), "=r"(v.y) : "r"(a) : "memory");
    return v;
}
__device__ __forceinline__ uint32_t lds1(uint32_t a) {
    uint32_t v;
    asm volatile("ld.shared.u32 %0, [%1];" : "=r"(v) : "r"(a) : "memory");
    return v;
}
__device__ __forceinline__ uint4 ldsm4t(uint32_t a) {
    uint4 v;
    asm volatile("ldmatrix.sync.aligned.m8n8.x4.trans.shared.b16 {%0,%1,%2,%3}, [%4];" : "=r"(v.x), "=r"(v.y), "=r"(v.z), "=r"(v.w) : "r"(a) : "memory");
    return v;
}
__device__ __forceinline__ void mma16816(float* d, uint4 a, uint32_t b0, uint32_t b1) {
    asm volatile("mma.sync.aligned.m16n8k16.row.col.f32.bf16.bf16.f32 {%0,%1,%2,%3}, {%4,%5,%6,%7}, {%8,%9}, {%0,%1,%2,%3};"
                 : "+f"(d[0]), "+f"(d[1]), "+f"(d[2]), "+f"(d[3]) : "r"(a.x), "r"(a.y), "r"(a.z), "r"(a.w), "r"(b0), "r"(b1));
}
__device__ __forceinline__ void fma8(float* acc, float s, uint4 w) {
    acc[0] = fmaf(s, bf_lo(w.x), acc[0]); acc[1] = fmaf(s, bf_hi(w.x), acc[1]);
    acc[2] = fmaf(s, bf_lo(w.y), acc[2]); acc[3] = fmaf(s, bf_hi(w.y), acc[3]);
    acc[4] = fmaf(s, bf_lo(w.z), acc[4]); acc[5] = fmaf(s, bf_hi(w.z), acc[5]);
    acc[6] = fmaf(s, bf_lo(w.w), acc[6]); acc[7] = fmaf(s, bf_hi(w.w), acc[7]);
}
__device__ __forceinline__ void ln_finish(float mean, float var, float& mean_b, float& rden) {
    mean_b = bfr(mean);
    float sq;
    asm("sqrt.approx.ftz.f32 %0, %1;" : "=f"(sq) : "f"(bfr(bfr(fmaxf(var, 0.f)) + 1e-5f)));
    rden = rcp(bfr(sq));
}
__device__ __forceinline__ float sel4(bool b0, bool b1, float v0, float v1, float v2, float v3) {
    float lo, hi, r;
    asm("{\n.reg .pred p;\nsetp.ne.u32 p, %3, 0;\nselp.f32 %0, %2, %1, p;\n}" : "=f"(lo) : "f"(v0), "f"(v1), "r"((uint32_t)b0));
    asm("{\n.reg .pred p;\nsetp.ne.u32 p, %3, 0;\nselp.f32 %0, %2, %1, p;\n}" : "=f"(hi) : "f"(v2), "f"(v3), "r"((uint32_t)b0));
    asm("{\n.reg .pred p;\nsetp.ne.u32 p, %3, 0;\nselp.f32 %0, %2, %1, p;\n}" : "=f"(r) : "f"(lo), "f"(hi), "r"((uint32_t)b1));
    return r;
}
__device__ __forceinline__ void sts2(uint32_t a, float v0, float v1) {
    asm volatile("st.shared.v2.f32 [%0], {%1,%2};" ::"r"(a), "f"(v0), "f"(v1) : "memory");
}
__device__ __forceinline__ void mb_st2(uint32_t* p, uint32_t a, uint32_t b) {
    asm volatile("st.relaxed.gpu.global.v2.u32 [%0], {%1,%2};" ::"l"(p), "r"(a), "r"(b) : "memory");
}
__device__ __forceinline__ void send_tiles(const float (&d)[5][4], uint32_t* p03, uint32_t* p4, int lane, uint32_t tag) {
    const bool b0 = lane & 1, b1 = lane & 2;
    mb_st2(p03, mb_enc(sel4(b0, b1, d[0][0], d[1][0], d[2][0], d[3][0]), tag), mb_enc(sel4(b0, b1, d[0][2], d[1][2], d[2][2], d[3][2]), tag));
    if ((lane & 3) == 0) mb_st2(p4, mb_enc(d[4][0], tag), mb_enc(d[4][2], tag));
}

struct Ptrs {
    const __nv_bfloat16 *k, *v, *x;
    Scratch* sc;
    const __nv_bfloat16 *wo, *wd;
    __nv_bfloat16* out;
};
struct alignas(64) Maps { CUtensorMap w0, wq, wg, wu; };

__global__ void __launch_bounds__(NTHREADS, 1) fused_decode_kernel(const Ptrs p, const __grid_constant__ Maps tm) {
    extern __shared__ __align__(1024) unsigned char smem[];
    const int tid = threadIdx.x, warp = tid >> 5, lane = tid & 31, bid = blockIdx.x;
    const uint32_t sbase = smem_u32(smem);
    const uint32_t bar_full = sbase + SM_BAR, bar_empty = sbase + SM_BAR + 64;
    const uint32_t bar_wq = sbase + SM_BAR + 192, bar_x = bar_wq + 16, bar_q0 = bar_wq + 24, bar_ffn = bar_wq + 32;
    volatile int* s_tile = reinterpret_cast<volatile int*>(smem + SM_BAR + 128);
    volatile int* s_qready = s_tile + 8;
    volatile uint32_t* s_tag = reinterpret_cast<volatile uint32_t*>(s_tile + 9);
    float* s_wp = reinterpret_cast<float*>(smem + SM_WP);
    float* s_x = reinterpret_cast<float*>(smem + SM_X);
    float* s_xn = reinterpret_cast<float*>(smem + SM_XN);
    uint32_t* const g_ticket = p.sc->ticket;
    uint32_t* const g_epoch = p.sc->epoch;
    uint32_t* const g_q0 = p.sc->q0;
    uint32_t* const g_q = p.sc->q;
    uint32_t* const g_part = p.sc->part;
    uint32_t* const g_h2 = p.sc->h2;
    uint32_t* const g_h3 = p.sc->h3;
    const bool streaming = bid < G;
    const char* kb = reinterpret_cast<const char*>(p.k);
    const char* vb = reinterpret_cast<const char*>(p.v);
    uint64_t pol = 0;
    auto startup_bar = [&](int i) { return i < 2 ? bar_full + 8 * i : i < 4 ? bar_wq + 8 * (i - 2) : bar_full + 8 * (i - 2); };
    auto startup_item = [&](int i) {
        if (i == 2 || i == 3) {
            if (bid < DH / 48) {
                mbar_arrive(startup_bar(i));
                return;
            }
            mbar_expect_tx(startup_bar(i), 320 * 96);
#pragma unroll
            for (int r = 2 * (i - 2); r < 2 * (i - 2) + 2; r++)
                tensor_load2d(sbase + SM_W + r * 160 * 96, &tm.wq, bid * 48, r * 160, startup_bar(i), pol);
        } else {
            const int sg = i < 2 ? i : i - 2;
            const unsigned t = sg * G + bid;
            s_tile[sg] = (int)t;
            mbar_expect_tx(startup_bar(i), STAGE_BYTES);
            bulk_load(sbase + SM_RING + sg * STAGE_BYTES, kb + (size_t)t * TILE_BYTES, TILE_BYTES, startup_bar(i), pol);
            bulk_load(sbase + SM_RING + sg * STAGE_BYTES + TILE_BYTES, vb + (size_t)t * TILE_BYTES, TILE_BYTES, startup_bar(i), pol);
        }
    };
    if (tid == 256) {
        asm volatile("createpolicy.fractional.L2::evict_first.b64 %0, 1.0;" : "=l"(pol));
#pragma unroll
        for (int i = 0; i < W0; i++) mbar_init(bar_full + 8 * i, 1);
        mbar_init(bar_x, 1);
        if (streaming) {
#pragma unroll
            for (int i = 0; i < W0; i++) startup_item(i);
        }
        mbar_expect_tx(bar_x, 16 + D * 2 + (bid < NQ0 ? 160 * 32 : 0));
        bulk_load(sbase + SM_XR, p.x, D * 2, bar_x, pol);
        bulk_load(sbase + SM_EP, g_epoch, 16, bar_x, pol);
        if (bid < NQ0) tensor_load2d(sbase + SM_W0, &tm.w0, (bid % 12) * 16, (bid / 12) * 160, bar_x, pol);
    }
    if (warp == 8) {
        if (lane == 0) {
#pragma unroll
            for (int i = W0; i < NS0; i++) mbar_init(bar_full + 8 * i, 1);
#pragma unroll
            for (int i = 0; i < NS0; i++) mbar_init(bar_empty + 8 * i, 8);
#pragma unroll
            for (int i = 0; i < 2; i++) mbar_init(bar_wq + 8 * i, 1);
#pragma unroll
            for (int i = 0; i < 3; i++) mbar_init(bar_ffn + 8 * i, 1);
            mbar_init(bar_q0, 1);
            *s_qready = 0;
            asm volatile("fence.proxy.async.shared::cta;" ::: "memory");
        }
        __syncwarp();
        asm volatile("bar.arrive 2, %0;" ::"n"(NTHREADS) : "memory");
        if (lane != 0) return;
        if (streaming) {
            unsigned nxt;
            asm volatile("atom.relaxed.gpu.global.add.u32 %0, [%1], 1;" : "=r"(nxt) : "l"(g_ticket) : "memory");
#pragma unroll
            for (int i = W0; i < NS0 + 2; i++) {
                mbar_wait(startup_bar(i - W0), 0);
                startup_item(i);
            }
            int st = 0;
            uint32_t ph = 0;
            while (true) {
                mbar_wait(bar_empty + 8 * st, ph);
                const unsigned t = NS0 * G + nxt;
                if (t >= NTILES) break;
                asm volatile("atom.relaxed.gpu.global.add.u32 %0, [%1], 1;" : "=r"(nxt) : "l"(g_ticket) : "memory");
                s_tile[st] = (int)t;
                mbar_expect_tx(bar_full + 8 * st, STAGE_BYTES);
                const uint32_t dst = sbase + SM_RING + st * STAGE_BYTES;
                bulk_load(dst, kb + (size_t)t * TILE_BYTES, TILE_BYTES, bar_full + 8 * st, pol);
                bulk_load(dst + TILE_BYTES, vb + (size_t)t * TILE_BYTES, TILE_BYTES, bar_full + 8 * st, pol);
                if (++st == NST) { st = 0; ph ^= 1; }
            }
            s_tile[st] = NTILES;
            mbar_arrive(bar_full + 8 * st);
            if (bid < NF) {
                unsigned it = 0;
                while (*s_qready < H) { if (++it > SPIN_LIMIT) __trap(); }
                mbar_wait(bar_full + 8 * (st == 0 ? NST - 1 : st - 1), st == 0 ? ph : ph ^ 1);
#pragma unroll 1
                for (int c = 0; c < 2; c++) {
                    mbar_expect_tx(bar_ffn + 8 * c, 2 * 320 * 32);
#pragma unroll
                    for (int r = 2 * c; r < 2 * c + 2; r++) tensor_load2d(sbase + SM_W + r * 160 * 32, &tm.wg, bid * 16, r * 160, bar_ffn + 8 * c, pol);
#pragma unroll
                    for (int r = 2 * c; r < 2 * c + 2; r++) tensor_load2d(sbase + SM_WU + r * 160 * 32, &tm.wu, bid * 16, r * 160, bar_ffn + 8 * c, pol);
                }
                mbar_wait(bar_ffn, 0);
                mbar_expect_tx(bar_ffn + 16, 16 * D * 2);
#pragma unroll 1
                for (int r = 0; r < 16; r++)
                    bulk_load(sbase + SM_WD + r * ROWP, p.wd + (size_t)(bid * 16 + r) * D, D * 2, bar_ffn + 16, pol);
            }
        } else {
            int st = 0;
            uint32_t ph = 1;
            for (int h = 0; h < H; h++) {
                if (h >= WO_ST) mbar_wait(bar_empty + 8 * st, ph);
                mbar_expect_tx(bar_full + 8 * st, DC * D * 2);
#pragma unroll 1
                for (int r = 0; r < DC; r++)
                    bulk_load(sbase + SM_RING + st * WO_BYTES + r * ROWP, p.wo + (size_t)(h * DH + (bid - G) * DC + r) * D, D * 2,
                              bar_full + 8 * st, pol);
                if (++st == WO_ST) { st = 0; ph ^= 1; }
            }
        }
        return;
    }
    if (warp == 9) {
        asm volatile("bar.sync 2, %0;" ::"n"(NTHREADS) : "memory");
        mbar_wait(bar_x, 0);
        const uint32_t tag = (lds1(sbase + SM_EP) & 1u) ^ 1u;
        uint2 xraw[5];
#pragma unroll
        for (int i = 0; i < 5; i++) xraw[i] = lds2(sbase + SM_XR + (i * 32 + lane) * 8);
        if (lane == 0) *s_tag = tag;
        if (!streaming) {
            __syncwarp();
            if (lane == 0) mbar_arrive(bar_q0);
            return;
        }
        uint32_t* s_xp = reinterpret_cast<uint32_t*>(smem + SM_XP);
        uint2* s_q = reinterpret_cast<uint2*>(smem + SM_Q);
        {
            float4 xv[5];
#pragma unroll
            for (int i = 0; i < 5; i++) xv[i] = make_float4(bf_lo(xraw[i].x), bf_hi(xraw[i].x), bf_lo(xraw[i].y), bf_hi(xraw[i].y));
            const float s0 = __shfl_sync(0xffffffffu, xv[0].x, 0);
            float s1 = 0.f, s2 = 0.f;
#pragma unroll
            for (int i = 0; i < 5; i++) {
                const float a = xv[i].x - s0, b = xv[i].y - s0, c = xv[i].z - s0, d = xv[i].w - s0;
                s1 += (a + b) + (c + d);
                s2 += (a * a + b * b) + (c * c + d * d);
            }
#pragma unroll
            for (int o = 16; o > 0; o >>= 1) {
                s1 += __shfl_xor_sync(0xffffffffu, s1, o);
                s2 += __shfl_xor_sync(0xffffffffu, s2, o);
            }
            const float e1 = s1 * (1.0f / D);
            float mb, rden;
            ln_finish(s0 + e1, s2 * (1.0f / D) - e1 * e1, mb, rden);
#pragma unroll
            for (int i = 0; i < 5; i++) {
                const uint32_t lo = pack_bf2(bfr(xv[i].x - mb) * rden, bfr(xv[i].y - mb) * rden);
                const uint32_t hi = pack_bf2(bfr(xv[i].z - mb) * rden, bfr(xv[i].w - mb) * rden);
                reinterpret_cast<float4*>(s_x)[i * 32 + lane] = xv[i];
                reinterpret_cast<float4*>(s_xn)[i * 32 + lane] = make_float4(bf_lo(lo), bf_hi(lo), bf_lo(hi), bf_hi(hi));
                reinterpret_cast<uint2*>(s_xp)[i * 32 + lane] = make_uint2(lo, hi);
            }
            __syncwarp();
        }
        if (bid < NQ0) {
            float acc[8] = {0.f, 0.f, 0.f, 0.f, 0.f, 0.f, 0.f, 0.f};
#pragma unroll
            for (int i = 0; i < 10; i++) fma8(acc, s_xn[(bid / 12) * 160 + (lane >> 1) + 16 * i], lds4(sbase + SM_W0 + (i * 32 + lane) * 16));
            const bool u1 = lane & 16, u2 = lane & 8, u3 = lane & 4;
            float r4[4], r2[2];
#pragma unroll
            for (int i = 0; i < 4; i++) r4[i] = (u1 ? acc[i + 4] : acc[i]) + __shfl_xor_sync(0xffffffffu, u1 ? acc[i] : acc[i + 4], 16);
#pragma unroll
            for (int i = 0; i < 2; i++) r2[i] = (u2 ? r4[i + 2] : r4[i]) + __shfl_xor_sync(0xffffffffu, u2 ? r4[i] : r4[i + 2], 8);
            float r1 = (u3 ? r2[1] : r2[0]) + __shfl_xor_sync(0xffffffffu, u3 ? r2[0] : r2[1], 4);
            r1 += __shfl_xor_sync(0xffffffffu, r1, 2);
            if (!(lane & 2))
                mb_st(&g_q0[(bid / 12) * DH + (bid % 12) * 16 + (lane & 1) * 8 + (u1 ? 4 : 0) + (u2 ? 2 : 0) + (u3 ? 1 : 0)], mb_enc(r1, tag));
        }
        {
            uint4 a[8];
            uint32_t miss[8];
#pragma unroll
            for (int i = 0; i < 8; i++) { a[i] = make_uint4(0u, 0u, 0u, 0u); miss[i] = 1u; }
            unsigned it = 0;
            while (true) {
#pragma unroll
                for (int i = 0; i < 8; i++) mb_ld4_if(a[i], g_q0 + (i < 4 ? lane * 4 : 128 + (lane & 15) * 4) + (i & 3) * DH, miss[i]);
                uint32_t any = 0u;
#pragma unroll
                for (int i = 0; i < 8; i++) { miss[i] &= mb_miss(a[i], tag); any |= miss[i]; }
                if (!any) break;
                if (++it > SPIN_LIMIT) __trap();
            }
            const uint4* b = a + 4;
            s_q[lane] = make_uint2(pack_bf2(F4SUM(a, x), F4SUM(a, y)), pack_bf2(F4SUM(a, z), F4SUM(a, w)));
            if (lane < 16) s_q[32 + lane] = make_uint2(pack_bf2(F4SUM(b, x), F4SUM(b, y)), pack_bf2(F4SUM(b, z), F4SUM(b, w)));
            __syncwarp();
            if (lane == 0) mbar_arrive(bar_q0);
        }
        mbar_wait(bar_wq, 0);
        mbar_wait(bar_wq + 8, 0);
        {
            const int g8 = lane >> 2, c4 = lane & 3, mj = lane >> 3, mr = lane & 7;
            float dq[3][4];
#pragma unroll
            for (int t = 0; t < 3; t++) dq[t][0] = dq[t][1] = dq[t][2] = dq[t][3] = 0.f;
            const uint32_t a0 = sbase + SM_W + ((mj >> 1) * 8 + mr) * 96 + (mj & 1) * 16;
            const int steps = bid < DH / 48 ? 0 : 40;
#pragma unroll 4
            for (int s = 0; s < steps; s++) {
                const uint32_t b0 = s_xp[s * 8 + c4], b1 = s_xp[s * 8 + 4 + c4];
#pragma unroll
                for (int t = 0; t < 3; t++) mma16816(dq[t], ldsm4t(a0 + s * 16 * 96 + t * 32), b0, b1);
            }
            if (c4 < 3) {
                const float v0 = c4 == 0 ? dq[0][0] : c4 == 1 ? dq[1][0] : dq[2][0];
                const float v1 = c4 == 0 ? dq[0][2] : c4 == 1 ? dq[1][2] : dq[2][2];
                mb_st(&g_q[bid * 48 + c4 * 16 + g8], mb_enc(bfr(v0), tag));
                mb_st(&g_q[bid * 48 + c4 * 16 + 8 + g8], mb_enc(bfr(v1), tag));
            }
        }
#pragma unroll 1
        for (int h0 = 1; h0 < H; h0 = (h0 + 4) & ~3) {
            uint4 a[6];
            mb_poll(a, g_q + ((h0 & ~3) * (DH / 4) + lane) * 4, 128, tag);
#pragma unroll
            for (int i = 0; i < 6; i++)
                if (h0 > 1 || i * 32 + lane >= DH / 4)
                    s_q[(h0 & ~3) * (DH / 4) + i * 32 + lane] = make_uint2((a[i].x >> 16) | (a[i].y & 0xffff0000u), (a[i].z >> 16) | (a[i].w & 0xffff0000u));
            __syncwarp();
            if (lane == 0) {
                asm volatile("fence.acq_rel.cta;" ::: "memory");
                *s_qready = (h0 + 4) & ~3;
            }
        }
        return;
    }
    asm volatile("bar.sync 2, %0;" ::"n"(NTHREADS) : "memory");

    if (streaming) {
        const int j = lane & 7;
        const uint32_t k_off = (warp * 4 + (lane >> 3)) * (DH * 2) + j * 16;
        const uint32_t v_off = TILE_BYTES + warp * 4 * (DH * 2);
        const bool mb_owner = warp < NC && lane < 14;
        uint32_t* const mb_base = g_part + (warp * G + bid) * SLOT_P + lane * 4;
        const uint32_t mb_col = (lane < 12 ? warp * DC + lane * 4 : 192) * 4;
        uint4 chk = make_uint4(0u, 0u, 0u, 0u);

        float q[24], o[6];
        float m = -3.0e38f, l = 0.f;
#pragma unroll
        for (int i = 0; i < 6; i++) o[i] = 0.f;
        int head = -1;
        int st = 0, nst = NS0;
        uint32_t ph = 0;
        mbar_wait(bar_q0, 0);
        bool last = false;
        while (true) {
            const uint32_t sa = sbase + SM_RING + st * STAGE_BYTES;
            uint4 kv[3];
            uint2 va[4];
            uint32_t vb2[4];
            int th = H;
            if (!last) {
                mbar_wait(bar_full + 8 * st, ph);
                th = s_tile[st] / TILES_PER_HEAD;
#pragma unroll
                for (int c = 0; c < 3; c++) kv[c] = lds4(sa + k_off + c * 128);
            }
            const uint32_t bar_rel = bar_empty + 8 * st;
            if (++st == nst) { st = 0; ph ^= 1; nst = NST; }

            if (th != head) {
                if (head < 0) head = 0;
#pragma unroll 1
                for (; head < th; head++) {
                    float* wp = s_wp + (head & 1) * 1600;
                    reinterpret_cast<float4*>(wp + warp * 196)[lane] = make_float4(o[0], o[1], o[2], o[3]);
                    reinterpret_cast<float2*>(wp + warp * 196 + 128)[lane] = make_float2(o[4], o[5]);
                    if (lane == 0) { reinterpret_cast<float4*>(wp + warp * 196)[48] = make_float4(l, 0.f, 0.f, 0.f); wp[1568 + warp] = m; }
                    cbar();
                    if (mb_owner) {
                        const uint32_t wa = sbase + SM_WP + (head & 1) * 6400;
                        const uint4 m0 = lds4(wa + 1568 * 4), m1 = lds4(wa + 1572 * 4);
                        uint4 pv[8];
#pragma unroll
                        for (int w = 0; w < 8; w++) pv[w] = lds4(wa + w * 196 * 4 + mb_col);
                        const float mw[8] = {__uint_as_float(m0.x), __uint_as_float(m0.y), __uint_as_float(m0.z), __uint_as_float(m0.w),
                                             __uint_as_float(m1.x), __uint_as_float(m1.y), __uint_as_float(m1.z), __uint_as_float(m1.w)};
                        float M8 = fmaxf(fmaxf(fmaxf(mw[0], mw[1]), fmaxf(mw[2], mw[3])), fmaxf(fmaxf(mw[4], mw[5]), fmaxf(mw[6], mw[7])));
                        M8 = __uint_as_float(mb_enc(M8, 1u));
                        float4 sa = make_float4(0.f, 0.f, 0.f, 0.f), sb = sa;
#pragma unroll
                        for (int w = 0; w < 8; w += 2) {
                            const float e = ex2(mw[w] - M8), e2 = ex2(mw[w + 1] - M8);
                            sa.x = fmaf(e, __uint_as_float(pv[w].x), sa.x); sa.y = fmaf(e, __uint_as_float(pv[w].y), sa.y);
                            sa.z = fmaf(e, __uint_as_float(pv[w].z), sa.z); sa.w = fmaf(e, __uint_as_float(pv[w].w), sa.w);
                            sb.x = fmaf(e2, __uint_as_float(pv[w + 1].x), sb.x); sb.y = fmaf(e2, __uint_as_float(pv[w + 1].y), sb.y);
                            sb.z = fmaf(e2, __uint_as_float(pv[w + 1].z), sb.z); sb.w = fmaf(e2, __uint_as_float(pv[w + 1].w), sb.w);
                        }
                        uint32_t* dst = mb_base + (head % RD) * (NC * G * SLOT_P);
                        unsigned it = 0;
                        while ((chk.x | chk.y | chk.z | chk.w) != 0u) { chk = mb_ld4(dst); if (++it > SPIN_LIMIT) __trap(); }
                        mb_st4(dst, make_uint4(mb_enc(sa.x + sb.x, 1u), mb_enc(lane < 12 ? sa.y + sb.y : M8, 1u), mb_enc(sa.z + sb.z, 1u),
                                               mb_enc(sa.w + sb.w, 1u)));
                        mb_ld4_if(chk, mb_base + ((head + 1) % RD) * (NC * G * SLOT_P), lane < 13 && head + 1 >= RD && head + 1 < H);
                    }
                    m = -3.0e38f; l = 0.f;
#pragma unroll
                    for (int i = 0; i < 6; i++) o[i] = 0.f;
                }
                if (th == H) break;
                if (head > 0) {
                    unsigned it = 0;
                    while (*s_qready <= head) { if (++it > SPIN_LIMIT) __trap(); }
                    asm volatile("fence.acq_rel.cta;" ::: "memory");
                }
#pragma unroll
                for (int c = 0; c < 3; c++) {
                    const uint4 u = lds4(sbase + SM_Q + head * (DH * 2) + c * 128 + j * 16);
                    q[c * 8 + 0] = bf_lo(u.x); q[c * 8 + 1] = bf_hi(u.x); q[c * 8 + 2] = bf_lo(u.y); q[c * 8 + 3] = bf_hi(u.y);
                    q[c * 8 + 4] = bf_lo(u.z); q[c * 8 + 5] = bf_hi(u.z); q[c * 8 + 6] = bf_lo(u.w); q[c * 8 + 7] = bf_hi(u.w);
                }
            }
            float d0 = 0.f, d1 = 0.f, d2 = 0.f, d3 = 0.f;
#pragma unroll
            for (int c = 0; c < 3; c++) {
                d0 = fmaf(q[c * 8 + 0], bf_lo(kv[c].x), d0); d1 = fmaf(q[c * 8 + 1], bf_hi(kv[c].x), d1);
                d2 = fmaf(q[c * 8 + 2], bf_lo(kv[c].y), d2); d3 = fmaf(q[c * 8 + 3], bf_hi(kv[c].y), d3);
                d0 = fmaf(q[c * 8 + 4], bf_lo(kv[c].z), d0); d1 = fmaf(q[c * 8 + 5], bf_hi(kv[c].z), d1);
                d2 = fmaf(q[c * 8 + 6], bf_lo(kv[c].w), d2); d3 = fmaf(q[c * 8 + 7], bf_hi(kv[c].w), d3);
            }
            float s = (d0 + d1) + (d2 + d3);
            asm volatile("" : "+f"(s));
            s += __shfl_xor_sync(0xffffffffu, s, 1);
#pragma unroll
            for (int i = 0; i < 4; i++) {
                va[i] = lds2(sa + v_off + i * (DH * 2) + lane * 8);
                vb2[i] = lds1(sa + v_off + i * (DH * 2) + 256 + lane * 4);
            }
            __syncwarp();
            if (lane == 0) mbar_arrive(bar_rel);
            const bool nready = mbar_test(bar_full + 8 * st, ph);
            last = __all_sync(0xffffffffu, s_tile[st] >= NTILES && nready);
            s += __shfl_xor_sync(0xffffffffu, s, 2);
            s += __shfl_xor_sync(0xffffffffu, s, 4);
            s = bfr(bfr(s) * 0.07216878364870322f) * 1.4426950408889634f;
            float sk[4];
#pragma unroll
            for (int i = 0; i < 4; i++) sk[i] = __shfl_sync(0xffffffffu, s, i * 8);
            const float mn = fmaxf(fmaxf(m, fmaxf(sk[0], sk[1])), fmaxf(sk[2], sk[3]));
            const float al = ex2(m - mn);
            m = mn;
            l *= al;
#pragma unroll
            for (int i = 0; i < 6; i++) o[i] *= al;
#pragma unroll
            for (int i = 0; i < 4; i++) {
                const float pr = ex2(sk[i] - mn);
                l += pr;
                o[0] = fmaf(pr, bf_lo(va[i].x), o[0]); o[1] = fmaf(pr, bf_hi(va[i].x), o[1]);
                o[2] = fmaf(pr, bf_lo(va[i].y), o[2]); o[3] = fmaf(pr, bf_hi(va[i].y), o[3]);
                o[4] = fmaf(pr, bf_lo(vb2[i]), o[4]);  o[5] = fmaf(pr, bf_hi(vb2[i]), o[5]);
            }
        }
        const uint32_t tag = *s_tag;
        if (bid >= NF) {
            const int rb = bid - NF;
            if (rb < NR) {
                float* s_rd = s_wp;
                const int wd = (lane & 7) * 4 + (lane >> 3);
                const int col = rb * 32 + (wd & 16) + ((wd & 15) >> 1) + (wd & 1) * 8;
                __nv_bfloat16* const dst = pin(p.out + col);
                const uint32_t* const src3 = g_h3 + rb * NF * 32 + tid * 4;
                uint4 a[3];
#pragma unroll
                for (int i = 0; i < 3; i++) a[i] = mb_ld4(src3 + i * 1024);
                float hres = 0.f;
                if (warp == 0) {
                    uint4 b[NC];
                    const int tl = rb * 2 + ((lane >> 2) & 1);
                    mb_poll(b, g_h2 + (tl / 5) * 96 + (tl % 5) * 16 + (lane & 3) * 4, H2P, tag);
                    const int k = lane >> 3;
                    const float at = k == 0 ? F4SUM(b, x) : k == 1 ? F4SUM(b, y) : k == 2 ? F4SUM(b, z) : F4SUM(b, w);
                    hres = bfr(s_x[col] + bfr(at));
                    __syncwarp();
                    if (rb == 0 && lane < 8) mb_st(g_epoch + lane, tag);
                }
                cbar();
                mb_poll<3, false>(a, src3, 1024, tag);
                __syncwarp();
                const float s0 = __uint_as_float(a[0].x) + __uint_as_float(a[1].x) + __uint_as_float(a[2].x);
                const float s1 = __uint_as_float(a[0].y) + __uint_as_float(a[1].y) + __uint_as_float(a[2].y);
                const float s2 = __uint_as_float(a[0].z) + __uint_as_float(a[1].z) + __uint_as_float(a[2].z);
                const float s3 = __uint_as_float(a[0].w) + __uint_as_float(a[1].w) + __uint_as_float(a[2].w);
                const bool u1 = lane & 16, u2 = lane & 8;
                const float t0 = (u1 ? s2 : s0) + __shfl_xor_sync(0xffffffffu, u1 ? s0 : s2, 16);
                const float t1 = (u1 ? s3 : s1) + __shfl_xor_sync(0xffffffffu, u1 ? s1 : s3, 16);
                s_rd[warp * 32 + lane] = (u2 ? t1 : t0) + __shfl_xor_sync(0xffffffffu, u2 ? t0 : t1, 8);
                cbar();
                if (warp == 0) {
                    const float* sr = s_rd + lane;
                    const float s = ((sr[0] + sr[32]) + (sr[64] + sr[96])) + ((sr[128] + sr[160]) + (sr[192] + sr[224]));
                    *reinterpret_cast<unsigned short*>(dst) = (unsigned short)pack_bf2(hres + bfr(s), 0.f);
                }
            }
            return;
        }

        const int g8 = lane >> 2, c4 = lane & 3;
        uint4 ag[5], au[5], ad[5];
        uint4 a[NC];
        const uint32_t* const src2 = g_h2 + warp * 96 + lane * 4;
#pragma unroll
        for (int c = 0; c < NC; c++) {
            a[c] = make_uint4(tag, tag, tag, tag);
            mb_ld4_if(a[c], src2 + c * H2P, lane < 20);
        }
        const int mj = lane >> 3, mr = lane & 7;
        mbar_wait(bar_ffn, 0);
        mbar_wait(bar_ffn + 8, 0);
#pragma unroll
        for (int s = 0; s < 5; s++) {
            const int row = warp * 80 + s * 16 + (mr & 6) + (mr & 1) * 8 + (mj >> 1);
            const uint32_t off = row * 32 + (((mj & 1) ^ ((row >> 2) & 1)) << 4);
            ag[s] = ldsm4t(sbase + SM_W + off);
            au[s] = ldsm4t(sbase + SM_WU + off);
        }
        {
            const int t3 = warp * 5 + c4, t4 = warp * 5 + 4;
            uint32_t* const dst3 = pin(g_h3 + ((t3 >> 1) * NF + bid) * RC + (t3 & 1) * 16 + g8 * 2);
            uint32_t* const dst4 = pin(g_h3 + ((t4 >> 1) * NF + bid) * RC + (t4 & 1) * 16 + g8 * 2);
            const uint32_t a_gu = sbase + SM_WP + 64 * 4, a_st = sbase + SM_WP;
            const float* xp = s_x + warp * 80 + (lane < 20 ? g8 * 16 + c4 * 2 : 0);
            const float4 xx = make_float4(xp[0], xp[8], xp[1], xp[9]);
            mb_poll<NC, false>(a, src2, H2P, tag);
            __syncwarp();
            const uint32_t t0 = pack_bf2(F4SUM(a, x), F4SUM(a, y)), t1 = pack_bf2(F4SUM(a, z), F4SUM(a, w));
            const uint32_t h0 = pack_bf2(xx.x + bf_lo(t0), xx.y + bf_hi(t0)), h1 = pack_bf2(xx.z + bf_lo(t1), xx.w + bf_hi(t1));
            constexpr uint32_t ONES = 0x3f803f80u;
            float dg[2][4], du[2][4], ds[2][4];
#pragma unroll
            for (int i = 0; i < 2; i++)
#pragma unroll
                for (int k = 0; k < 4; k++) dg[i][k] = du[i][k] = ds[i][k] = 0.f;
            uint32_t f0[5], f1[5];
#pragma unroll
            for (int s = 0; s < 5; s++) { f0[s] = __shfl_sync(0xffffffffu, h0, s * 4 + c4); f1[s] = __shfl_sync(0xffffffffu, h1, s * 4 + c4); }
#pragma unroll
            for (int s = 0; s < 5; s++) {
                const uint32_t b0 = g8 == 1 ? ONES : f0[s], b1 = g8 == 1 ? ONES : f1[s];
                mma16816(ds[s & 1], make_uint4(f0[s], ONES, f1[s], ONES), b0, b1);
                mma16816(dg[s & 1], ag[s], b0, b1);
                mma16816(du[s & 1], au[s], b0, b1);
            }
            if (c4 == 0) {
                const uint32_t aw = a_gu + (warp * 32 + g8) * 8;
                sts2(aw, dg[0][0] + dg[1][0], dg[0][1] + dg[1][1]);
                sts2(aw + 64, dg[0][2] + dg[1][2], dg[0][3] + dg[1][3]);
                sts2(aw + 128, du[0][0] + du[1][0], du[0][1] + du[1][1]);
                sts2(aw + 192, du[0][2] + du[1][2], du[0][3] + du[1][3]);
                if (lane == 0) sts2(a_st + warp * 8, ds[0][2] + ds[1][2], ds[0][0] + ds[1][0]);
            }
            mbar_wait(bar_ffn + 16, 0);
            cbar();
            uint4 pw[4];
#pragma unroll
            for (int i = 0; i < 4; i++) pw[i] = lds4(a_st + i * 16);
            uint2 sg[8];
#pragma unroll
            for (int w = 0; w < 8; w++) sg[w] = lds2(a_gu + (w * 32 + lane) * 8);
#pragma unroll
            for (int t = 0; t < 5; t++) ad[t] = ldsm4t(sbase + SM_WD + ((mj >> 1) * 8 + mr) * ROWP + (warp * 10 + 2 * t + (mj & 1)) * 16);
            const float mean = (F4SUM(pw, x) + F4SUM(pw, z)) * (1.0f / D);
            const float ex2m = (F4SUM(pw, y) + F4SUM(pw, w)) * (1.0f / D);
            float mb, rden;
            ln_finish(mean, fmaf(-mean, mean, ex2m), mb, rden);
            const uint2* sh = sg + 4;
            const float s = bfr(fmaf(-mb, F4SUM(sg, y) + F4SUM(sh, y), F4SUM(sg, x) + F4SUM(sh, x)) * rden);
            const float up = __shfl_down_sync(0xffffffffu, s, 16);
            const float act = bfr(s * rcp(1.0f + ex2(-1.4426950408889634f * s))) * up;
            const uint32_t c0 = pack_bf2(__shfl_sync(0xffffffffu, act, 2 * c4), __shfl_sync(0xffffffffu, act, 2 * c4 + 1));
            const uint32_t c1 = pack_bf2(__shfl_sync(0xffffffffu, act, 2 * c4 + 8), __shfl_sync(0xffffffffu, act, 2 * c4 + 9));
            float dd[5][4];
#pragma unroll
            for (int t = 0; t < 5; t++) {
                dd[t][0] = dd[t][1] = dd[t][2] = dd[t][3] = 0.f;
                mma16816(dd[t], ad[t], c0, c1);
            }
            send_tiles(dd, dst3, dst4, lane, tag);
        }
        return;
    }

    const int cj = bid - G;
    {
        const int c4 = lane & 3, cv = lane & 15, cg = warp * 2 + (lane >> 4);
        const int mj = lane >> 3, mr = lane & 7;
        mbar_wait(bar_q0, 0);
        const uint32_t tag = *s_tag;
        uint32_t* const dst2 = pin(g_h2 + cj * H2P + warp * 96 + (lane >> 2) * 2);
        float acc[5][4];
#pragma unroll
        for (int t = 0; t < 5; t++) acc[t][0] = acc[t][1] = acc[t][2] = acc[t][3] = 0.f;
        int st = 0;
        uint32_t ph = 0;
#pragma unroll 1
        for (int h = 0; h < H; h++) {
            uint4 aw[5][3];
            mbar_wait(bar_full + 8 * st, ph);
#pragma unroll
            for (int t = 0; t < 5; t++)
#pragma unroll
                for (int s = 0; s < 3; s++)
                    aw[t][s] = ldsm4t(sbase + SM_RING + st * WO_BYTES + (s * 16 + (mj >> 1) * 8 + mr) * ROWP + (warp * 10 + 2 * t + (mj & 1)) * 16);
            __syncwarp();
            if (lane == 0) mbar_arrive(bar_empty + 8 * st);
            if (++st == WO_ST) { st = 0; ph ^= 1; }

            uint32_t* slot = g_part + (((h % RD) * NC + cj) * G + cg) * SLOT_P + cv * 4;
            uint4 a[8];
            if (h < H - 1) {
                unsigned it = 0;
                while (!(mb_ld(slot) & 1u) && cv < 13) { __nanosleep(300); if (++it > SPIN_LIMIT) __trap(); }
            }
            if (h == H - 1) {
                unsigned it = 0;
                while (!__any_sync(0xffffffffu, mb_ld(slot - cv * 4 + (cv & 7) * 16 * SLOT_P) & 1u)) {
                    __nanosleep(100);
                    if (++it > SPIN_LIMIT) __trap();
                }
            }
            mb_poll(a, slot, 16 * SLOT_P, 1u, cv < 13);
            __syncwarp();
            float mi[8];
#pragma unroll
            for (int i = 0; i < 8; i++) mi[i] = __uint_as_float(__shfl_sync(0xffffffffu, a[i].y, (lane & 16) | 12));
            float mt = fmaxf(fmaxf(fmaxf(mi[0], mi[1]), fmaxf(mi[2], mi[3])), fmaxf(fmaxf(mi[4], mi[5]), fmaxf(mi[6], mi[7])));
            mt = fmaxf(mt, __shfl_xor_sync(0xffffffffu, mt, 16));
            float4 sa = make_float4(0.f, 0.f, 0.f, 0.f), sb = sa;
#pragma unroll
            for (int i = 0; i < 8; i += 2) {
                const float w = ex2(mi[i] - mt), w2 = ex2(mi[i + 1] - mt);
                sa.x = fmaf(w, __uint_as_float(a[i].x), sa.x); sa.y = fmaf(w, __uint_as_float(a[i].y), sa.y);
                sa.z = fmaf(w, __uint_as_float(a[i].z), sa.z); sa.w = fmaf(w, __uint_as_float(a[i].w), sa.w);
                sb.x = fmaf(w2, __uint_as_float(a[i + 1].x), sb.x); sb.y = fmaf(w2, __uint_as_float(a[i + 1].y), sb.y);
                sb.z = fmaf(w2, __uint_as_float(a[i + 1].z), sb.z); sb.w = fmaf(w2, __uint_as_float(a[i + 1].w), sb.w);
            }
            sa.x += sb.x; sa.y += sb.y; sa.z += sb.z; sa.w += sb.w;
            sa.x += __shfl_xor_sync(0xffffffffu, sa.x, 16); sa.y += __shfl_xor_sync(0xffffffffu, sa.y, 16);
            sa.z += __shfl_xor_sync(0xffffffffu, sa.z, 16); sa.w += __shfl_xor_sync(0xffffffffu, sa.w, 16);
            float* cp = s_wp + (h & 1) * 512;
            if (lane < 13) reinterpret_cast<float4*>(cp + warp * 52)[lane] = sa;
            if (lane == 0) cp[448 + warp] = mt;
            cbar();
            {
                const float4 m0 = reinterpret_cast<const float4*>(cp + 448)[0], m1 = reinterpret_cast<const float4*>(cp + 448)[1];
                const float mw[8] = {m0.x, m0.y, m0.z, m0.w, m1.x, m1.y, m1.z, m1.w};
                const float M = fmaxf(fmaxf(fmaxf(mw[0], mw[1]), fmaxf(mw[2], mw[3])), fmaxf(fmaxf(mw[4], mw[5]), fmaxf(mw[6], mw[7])));
                const int pi = lane < 24 ? lane : 24;
                float n0 = 0.f, n1 = 0.f, n2 = 0.f, n3 = 0.f;
#pragma unroll
                for (int w = 0; w < 8; w += 2) {
                    const float e = ex2(mw[w] - M), e2 = ex2(mw[w + 1] - M);
                    const float2 v = reinterpret_cast<const float2*>(cp + w * 52)[pi], v2 = reinterpret_cast<const float2*>(cp + (w + 1) * 52)[pi];
                    n0 = fmaf(e, v.x, n0); n1 = fmaf(e, v.y, n1);
                    n2 = fmaf(e2, v2.x, n2); n3 = fmaf(e2, v2.y, n3);
                }
                n0 += n2; n1 += n3;
                const float rd = rcp(__shfl_sync(0xffffffffu, n0, 24));
                const uint32_t pk = pack_bf2(n0 * rd, n1 * rd);
#pragma unroll
                for (int s = 0; s < 3; s++) {
                    const uint32_t b0 = __shfl_sync(0xffffffffu, pk, s * 8 + c4), b1 = __shfl_sync(0xffffffffu, pk, s * 8 + 4 + c4);
#pragma unroll
                    for (int t = 0; t < 5; t++) mma16816(acc[t], aw[t][s], b0, b1);
                }
            }
            if (h == H - 1) {
                send_tiles(acc, dst2 + c4 * 16, dst2 + 64, lane, tag);
                cbar();
            }
            if (cv < 13) {
#pragma unroll
                for (int i = 0; i < 8; i++) mb_st4(slot + i * 16 * SLOT_P, make_uint4(0u, 0u, 0u, 0u));
            }
        }
        if (cj == 0 && tid == 0) mb_st(g_ticket, 0u);
    }
}

constexpr int FB_SPLIT = 64;
__device__ float fb_q[HD], fb_part[H * FB_SPLIT * (DH + 2)], fb_o[HD], fb_h[D], fb_act[F];

__device__ void fb_layernorm(float* v, float* red) {
    const int tid = threadIdx.x;
    float mean = 0.f, var = 0.f;
    for (int pass = 0; pass < 2; pass++) {
        float a = 0.f;
        for (int i = tid; i < D; i += 256) a += pass ? (v[i] - mean) * (v[i] - mean) : v[i];
        red[tid] = a;
        __syncthreads();
        a = 0.f;
        for (int i = 0; i < 256; i++) a += red[i];
        __syncthreads();
        if (pass) var = a / D; else mean = a / D;
    }
    float mb, rden;
    ln_finish(mean, var, mb, rden);
    for (int i = tid; i < D; i += 256) v[i] = bfr(bfr(v[i] - mb) * rden);
    __syncthreads();
}
__device__ float fb_dot(const float* v, const __nv_bfloat16* w, int k, int pitch) {
    float a = 0.f;
    for (int i = 0; i < k; i++) a = fmaf(v[i], __bfloat162float(w[(size_t)i * pitch]), a);
    return bfr(a);
}
__global__ void fb_q_kernel(const __nv_bfloat16* x, const __nv_bfloat16* wq) {
    __shared__ float v[D], red[256];
    for (int i = threadIdx.x; i < D; i += 256) v[i] = __bfloat162float(x[i]);
    __syncthreads();
    fb_layernorm(v, red);
    const int n = blockIdx.x * 256 + threadIdx.x;
    fb_q[n] = fb_dot(v, wq + n, D, HD);
}
__global__ void fb_attn_kernel(const __nv_bfloat16* k, const __nv_bfloat16* v) {
    const int h = blockIdx.y, lane = threadIdx.x;
    float q[6], o[6] = {0.f, 0.f, 0.f, 0.f, 0.f, 0.f}, m = -3.0e38f, l = 0.f;
    for (int i = 0; i < 6; i++) q[i] = fb_q[h * DH + lane * 6 + i];
    for (int t = 0; t < SK / FB_SPLIT; t++) {
        const size_t row = ((size_t)h * SK + blockIdx.x * (SK / FB_SPLIT) + t) * DH + lane * 6;
        float s = 0.f;
        for (int i = 0; i < 6; i++) s = fmaf(q[i], __bfloat162float(k[row + i]), s);
        for (int of = 16; of > 0; of >>= 1) s += __shfl_xor_sync(0xffffffffu, s, of);
        s = bfr(bfr(s) * 0.07216878364870322f) * 1.4426950408889634f;
        const float mn = fmaxf(m, s), al = ex2(m - mn), pr = ex2(s - mn);
        m = mn;
        l = fmaf(l, al, pr);
        for (int i = 0; i < 6; i++) o[i] = fmaf(pr, __bfloat162float(v[row + i]), o[i] * al);
    }
    float* dst = fb_part + (h * FB_SPLIT + blockIdx.x) * (DH + 2);
    for (int i = 0; i < 6; i++) dst[lane * 6 + i] = o[i];
    if (lane == 0) { dst[DH] = l; dst[DH + 1] = m; }
}
__global__ void fb_combine_kernel() {
    const float* src = fb_part + blockIdx.x * FB_SPLIT * (DH + 2);
    float M = -3.0e38f, num = 0.f, den = 0.f;
    for (int c = 0; c < FB_SPLIT; c++) M = fmaxf(M, src[c * (DH + 2) + DH + 1]);
    for (int c = 0; c < FB_SPLIT; c++) {
        const float w = ex2(src[c * (DH + 2) + DH + 1] - M);
        num = fmaf(w, src[c * (DH + 2) + threadIdx.x], num);
        den = fmaf(w, src[c * (DH + 2) + DH], den);
    }
    fb_o[blockIdx.x * DH + threadIdx.x] = bfr(num / den);
}
__global__ void fb_wo_kernel(const __nv_bfloat16* x, const __nv_bfloat16* wo) {
    const int n = blockIdx.x * 128 + threadIdx.x;
    fb_h[n] = bfr(__bfloat162float(x[n]) + fb_dot(fb_o, wo + n, HD, D));
}
__global__ void fb_act_kernel(const __nv_bfloat16* wg, const __nv_bfloat16* wu) {
    __shared__ float v[D], red[256];
    for (int i = threadIdx.x; i < D; i += 256) v[i] = fb_h[i];
    __syncthreads();
    fb_layernorm(v, red);
    const int n = blockIdx.x * 256 + threadIdx.x;
    const float g = fb_dot(v, wg + n, D, F);
    fb_act[n] = bfr(bfr(g / (1.0f + __expf(-g))) * fb_dot(v, wu + n, D, F));
}
__global__ void fb_down_kernel(const __nv_bfloat16* wd, __nv_bfloat16* out) {
    const int n = blockIdx.x * 128 + threadIdx.x;
    out[n] = __float2bfloat16_rn(fb_h[n] + fb_dot(fb_act, wd + n, F, D));
}

typedef CUresult (*EncodeFn)(CUtensorMap*, CUtensorMapDataType, cuuint32_t, void*, const cuuint64_t*, const cuuint64_t*,
                             const cuuint32_t*, const cuuint32_t*, CUtensorMapInterleave, CUtensorMapSwizzle,
                             CUtensorMapL2promotion, CUtensorMapFloatOOBfill);

void encode2d(EncodeFn fn, CUtensorMap* tm, const void* base, uint64_t d0, uint64_t d1, uint32_t b0, uint32_t b1,
              CUtensorMapSwizzle sw, CUtensorMapL2promotion promo) {
    cuuint64_t dims[2] = {d0, d1};
    cuuint64_t strides[1] = {d0 * 2};
    cuuint32_t box[2] = {b0, b1};
    cuuint32_t es[2] = {1, 1};
    fn(tm, CU_TENSOR_MAP_DATA_TYPE_BFLOAT16, 2, const_cast<void*>(base), dims, strides, box, es, CU_TENSOR_MAP_INTERLEAVE_NONE,
       sw, promo, CU_TENSOR_MAP_FLOAT_OOB_FILL_NONE);
}

}

extern "C" void kernel_launch(void* const* d_in, const int* in_sizes, int n_in, void* d_out, int out_size) {
    (void)in_sizes; (void)n_in; (void)out_size;
    static EncodeFn encode = nullptr;
    static void* scratch = nullptr;
    static int resident = -1;
    if (resident < 0) {
        void* fn = nullptr;
        cudaDriverEntryPointQueryResult qr;
        cudaGetDriverEntryPoint("cuTensorMapEncodeTiled", &fn, cudaEnableDefault, &qr);
        encode = (EncodeFn)fn;
        cudaGetSymbolAddress(&scratch, g_scratch);
        cudaFuncSetAttribute(fused_decode_kernel, cudaFuncAttributeMaxDynamicSharedMemorySize, SMEM_BYTES);
        int dev = 0, sms = 0, per_sm = 0;
        cudaGetDevice(&dev);
        cudaDeviceGetAttribute(&sms, cudaDevAttrMultiProcessorCount, dev);
        cudaOccupancyMaxActiveBlocksPerMultiprocessor(&per_sm, fused_decode_kernel, NTHREADS, SMEM_BYTES);
        resident = encode ? sms * per_sm : 0;
    }
    const __nv_bfloat16* const* in = (const __nv_bfloat16* const*)d_in;
    cudaStream_t st = cudaStreamPerThread;
    if (resident < G + NC) {
        fb_q_kernel<<<HD / 256, 256, 0, st>>>(in[0], in[3]);
        fb_attn_kernel<<<dim3(FB_SPLIT, H), 32, 0, st>>>(in[1], in[2]);
        fb_combine_kernel<<<H, DH, 0, st>>>();
        fb_wo_kernel<<<D / 128, 128, 0, st>>>(in[0], in[4]);
        fb_act_kernel<<<F / 256, 256, 0, st>>>(in[6], in[7]);
        fb_down_kernel<<<D / 128, 128, 0, st>>>(in[8], (__nv_bfloat16*)d_out);
        return;
    }
    Ptrs p;
    p.x = in[0];
    p.k = in[1];
    p.v = in[2];
    p.wo = in[4];
    p.wd = in[8];
    p.out = (__nv_bfloat16*)d_out;
    p.sc = (Scratch*)scratch;
    Maps tm;
    encode2d(encode, &tm.wq, in[3], HD, D, 48, 160, CU_TENSOR_MAP_SWIZZLE_NONE, CU_TENSOR_MAP_L2_PROMOTION_L2_128B);
    encode2d(encode, &tm.w0, in[3], HD, D, 16, 160, CU_TENSOR_MAP_SWIZZLE_NONE, CU_TENSOR_MAP_L2_PROMOTION_NONE);
    encode2d(encode, &tm.wg, in[6], F, D, 16, 160, CU_TENSOR_MAP_SWIZZLE_32B, CU_TENSOR_MAP_L2_PROMOTION_L2_128B);
    encode2d(encode, &tm.wu, in[7], F, D, 16, 160, CU_TENSOR_MAP_SWIZZLE_32B, CU_TENSOR_MAP_L2_PROMOTION_L2_128B);
    fused_decode_kernel<<<G + NC, NTHREADS, SMEM_BYTES, st>>>(p, tm);
}
```
